```python
import torch

def _softmax(x, axis=-1):
    return torch.softmax(x, dim=axis)
def _gelu(x):
    return torch.nn.functional.gelu(x, approximate="tanh")
def _silu(x):
    return torch.nn.functional.silu(x)
def _sigmoid(x):
    return torch.sigmoid(x)
def _layernorm(x, axis=-1, eps=1e-5):
    m = x.mean(dim=axis, keepdim=True)
    v = x.var(dim=axis, keepdim=True, unbiased=False)
    return (x - m) / torch.sqrt(v + eps)
def _scatter_add(tgt, idx, src, axis=0):
    return tgt.clone().index_add_(axis, idx, src)
def _segment_sum(src, seg, n):
    out = torch.zeros((n,) + src.shape[1:], dtype=src.dtype)
    return out.index_add_(0, seg, src)
def _pad(x, pw):
    flat = tuple(v for pair in reversed(pw) for v in pair)
    return torch.nn.functional.pad(x, flat)

kernel_name = 'standalone__adm_resblock__diffusion'

def setup_inputs():

    _w = (lambda a: (lambda t: t.to(torch.bfloat16) if t.is_floating_point() else t)(torch.as_tensor(a)))
    B, C, HW, E = 2, 128, 64, 768
    sc = (9.0 * C) ** -0.5
    return {
        "x": _w((lambda *s: torch.randn(*s, dtype=torch.bfloat16) * 0.05)(B, C, HW, HW)),
        "t_emb": _w((lambda *s: torch.randn(*s, dtype=torch.bfloat16) * 0.4)(B, E)),
        "g1": _w(1.0 + 0.1 * (lambda *s: torch.randn(*s, dtype=torch.bfloat16) * 0.4)(C)),
        "be1": _w(0.1 * (lambda *s: torch.randn(*s, dtype=torch.bfloat16) * 0.4)(C)),
        "w1": _w((lambda *s: torch.randn(*s, dtype=torch.bfloat16) * 0.4)(C, C, 3, 3) * sc),
        "w_emb": _w((lambda *s: torch.randn(*s, dtype=torch.bfloat16) * 0.4)(E, C) * (E ** -0.5)),
        "g2": _w(1.0 + 0.1 * (lambda *s: torch.randn(*s, dtype=torch.bfloat16) * 0.4)(C)),
        "be2": _w(0.1 * (lambda *s: torch.randn(*s, dtype=torch.bfloat16) * 0.4)(C)),
        "w2": _w((lambda *s: torch.randn(*s, dtype=torch.bfloat16) * 0.4)(C, C, 3, 3) * sc),
    }

def reference(x, t_emb, g1, be1, w1, w_emb, g2, be2, w2):
    B, C, H, W = x.shape
    G, eps = 4, 1e-5
    def gn(z, gamma, beta):
        zr = z.reshape(B, G, (C // G) * H * W)
        mu = zr.mean(-1).reshape(B, G, 1)
        var = ((zr - mu) ** 2).mean(-1).reshape(B, G, 1)
        zn = ((zr - mu) / torch.sqrt(var + eps)).reshape(B, C, H, W)
        return zn * gamma.reshape(1, C, 1, 1) + beta.reshape(1, C, 1, 1)
    def conv3(z, w):
        zp = _pad(z, ((0, 0), (0, 0), (1, 1), (1, 1)))
        taps = [torch.einsum("bchw,oc->bohw", zp[:, :, i:i+H, j:j+W], w[:, :, i, j]) for i in range(3) for j in range(3)]
        out = taps[0]
        for t in taps[1:]:
            out = out + t
        return out
    h = conv3(_silu(gn(x, g1, be1)), w1)
    emb = _silu(t_emb) @ w_emb
    h = h + emb.reshape(B, C, 1, 1)
    h = conv3(_silu(gn(h, g2, be2)), w2)
    return x + h
```

```cpp
#include <cuda_runtime.h>
#include <cuda_bf16.h>
#include <cuda.h>
#include <stdint.h>

namespace {

constexpr int PLANE = 528;
constexpr int CHUNK = 10 * PLANE;
constexpr int OPSZ = 8 * CHUNK;
constexpr int WPIECE = 18432;
constexpr int WSZ = 4 * WPIECE;
constexpr int SM_WS = 0;
constexpr int SM_SA = WSZ;
constexpr int SM_SB = SM_SA + 32768;
constexpr int SM_OP1 = SM_SB + 32768;
constexpr int SM_OP0 = SM_OP1 + OPSZ;
constexpr int SM_MISC = SM_OP0 + OPSZ;
constexpr int B_ROWA = 0;
constexpr int B_FREE = 9;
constexpr int B_WFREE = 11;
constexpr int B_P = 13;
constexpr int B_ROW = 17;
constexpr int B_W2 = 25;
constexpr int B_SAFREE = 26;
constexpr int B_RES = 27;
constexpr int B_X1 = 29;
constexpr int B_S = 30;
constexpr int B_STAT = 38;
constexpr int B_W = 42;
constexpr int SM_PAR = SM_MISC + 448;
constexpr int SM_COEF = SM_MISC + 512;
constexpr int SM_RED = SM_COEF + 2560;
constexpr int SM_TS = SM_RED + 4352;
constexpr int SMEM_BYTES = SM_TS;
#define TIT 1
#define HDELAY2 500
#define XW0 0
#define XDELAY 700
#define HDELAY 400
constexpr int SPIN_LIMIT = 200000;

__device__ uint4 g_h[2 * 2 * 128 * 64 * 8];
__device__ __align__(128) uint4 g_box[336];
constexpr int BX_EMB = 1024, BX_FLAG = 5120;
__device__ uint4 g_w2f[4 * 36 * 128];
#define TS3(id) do { } while (0)
#define TS2(id) do { } while (0)
#define TS(id) do { } while (0)
#define TS_DUMP() do { } while (0)

__device__ __forceinline__ uint32_t smem_u32(const void* p) { return (uint32_t)__cvta_generic_to_shared(p); }
__device__ __forceinline__ void mbar_init(uint32_t bar, int cnt) {
    asm volatile("mbarrier.init.shared::cta.b64 [%0], %1;" ::"r"(bar), "r"(cnt) : "memory");
}
__device__ __forceinline__ void mbar_expect_tx(uint32_t bar, uint32_t bytes) {
    asm volatile("mbarrier.arrive.expect_tx.shared::cta.b64 _, [%0], %1;" ::"r"(bar), "r"(bytes) : "memory");
}
__device__ __forceinline__ void mbar_wait(uint32_t bar, uint32_t par) {
    asm volatile(
        "{\n"
        ".reg .pred p;\n"
        ".reg .u32 n;\n"
        "mov.u32 n, 0;\n"
        "WAIT_LOOP:\n"
        "mbarrier.try_wait.parity.shared::cta.b64 p, [%0], %1;\n"
        "add.u32 n, n, 1;\n"
        "setp.lt.and.u32 p, n, 100000, !p;\n"
        "@p bra.uni WAIT_LOOP;\n"
        "}\n" ::"r"(bar), "r"(par) : "memory");
}
__device__ __forceinline__ uint32_t clock32() {
    uint32_t c;
    asm volatile("mov.u32 %0, %%clock;" : "=r"(c));
    return c;
}
__device__ __forceinline__ bool elect_one() {
    uint32_t r;
    asm volatile("{.reg .pred p; elect.sync _|p, 0xffffffff; selp.u32 %0, 1, 0, p;}" : "=r"(r));
    return r;
}
__device__ __forceinline__ void wg_fence() { asm volatile("wgmma.fence.sync.aligned;" ::: "memory"); }
__device__ __forceinline__ void wg_commit() { asm volatile("wgmma.commit_group.sync.aligned;" ::: "memory"); }
template <int N> __device__ __forceinline__ void wg_wait() {
    asm volatile("wgmma.wait_group.sync.aligned %0;" ::"n"(N) : "memory");
}
__device__ __forceinline__ void wgmma_acc(float (&d)[32], const uint32_t* a, uint64_t desc) {
    asm volatile(
        "wgmma.mma_async.sync.aligned.m64n64k16.f32.bf16.bf16 "
        "{%0,%1,%2,%3,%4,%5,%6,%7,%8,%9,%10,%11,%12,%13,%14,%15,%16,%17,%18,%19,%20,%21,%22,%23,%24,%25,%26,%27,%28,%29,%30,%31}, "
        "{%32,%33,%34,%35}, %36, 1, 1, 1, 0;\n"
        : "+f"(d[0]), "+f"(d[1]), "+f"(d[2]), "+f"(d[3]), "+f"(d[4]), "+f"(d[5]), "+f"(d[6]), "+f"(d[7]), "+f"(d[8]), "+f"(d[9]), "+f"(d[10]), "+f"(d[11]), "+f"(d[12]), "+f"(d[13]), "+f"(d[14]), "+f"(d[15]), "+f"(d[16]), "+f"(d[17]), "+f"(d[18]), "+f"(d[19]), "+f"(d[20]), "+f"(d[21]), "+f"(d[22]), "+f"(d[23]), "+f"(d[24]), "+f"(d[25]), "+f"(d[26]), "+f"(d[27]), "+f"(d[28]), "+f"(d[29]), "+f"(d[30]), "+f"(d[31])
        : "r"(a[0]), "r"(a[1]), "r"(a[2]), "r"(a[3]), "l"(desc));
}
__device__ __forceinline__ void wgmma_first(float (&d)[32], const uint32_t* a, uint64_t desc) {
    asm volatile(
        "wgmma.mma_async.sync.aligned.m64n64k16.f32.bf16.bf16 "
        "{%0,%1,%2,%3,%4,%5,%6,%7,%8,%9,%10,%11,%12,%13,%14,%15,%16,%17,%18,%19,%20,%21,%22,%23,%24,%25,%26,%27,%28,%29,%30,%31}, "
        "{%32,%33,%34,%35}, %36, 0, 1, 1, 0;\n"
        : "=f"(d[0]), "=f"(d[1]), "=f"(d[2]), "=f"(d[3]), "=f"(d[4]), "=f"(d[5]), "=f"(d[6]), "=f"(d[7]), "=f"(d[8]), "=f"(d[9]), "=f"(d[10]), "=f"(d[11]), "=f"(d[12]), "=f"(d[13]), "=f"(d[14]), "=f"(d[15]), "=f"(d[16]), "=f"(d[17]), "=f"(d[18]), "=f"(d[19]), "=f"(d[20]), "=f"(d[21]), "=f"(d[22]), "=f"(d[23]), "=f"(d[24]), "=f"(d[25]), "=f"(d[26]), "=f"(d[27]), "=f"(d[28]), "=f"(d[29]), "=f"(d[30]), "=f"(d[31])
        : "r"(a[0]), "r"(a[1]), "r"(a[2]), "r"(a[3]), "l"(desc));
}
__device__ __forceinline__ void acc_fence(float (&d)[32]) {
#pragma unroll
    for (int i = 0; i < 32; i++) asm volatile("" : "+f"(d[i])::"memory");
}
template <int SUB>
__device__ __forceinline__ void mma_sub(float (&acc)[32], const uint32_t (&W)[144], uint64_t dcen) {
    constexpr int RG = SUB / 4, KS = SUB % 4;
    constexpr int TI = RG == 0 ? 1 : (RG == 1 ? 2 : 0);
    constexpr int ROFF = (TI - 1) * 8;
#pragma unroll
    for (int dx = 0; dx < 3; dx++) {
        uint64_t d = dcen + (uint64_t)(int64_t)(KS * (2 * CHUNK / 16) + dx * (PLANE / 16) + ROFF);
        if (SUB == 0 && dx == 0) wgmma_first(acc, &W[(KS * 9 + TI * 3 + dx) * 4], d);
        else wgmma_acc(acc, &W[(KS * 9 + TI * 3 + dx) * 4], d);
    }
}
__device__ __forceinline__ uint4 ldg_nc(const void* p) {
    uint4 v;
    asm volatile("ld.global.nc.L1::no_allocate.v4.u32 {%0,%1,%2,%3}, [%4];"
                 : "=r"(v.x), "=r"(v.y), "=r"(v.z), "=r"(v.w) : "l"(p));
    return v;
}
__device__ __forceinline__ uint4 ldg_rlx(const void* p) {
    uint4 v;
    asm volatile("ld.relaxed.gpu.global.v4.u32 {%0,%1,%2,%3}, [%4];"
                 : "=r"(v.x), "=r"(v.y), "=r"(v.z), "=r"(v.w) : "l"(p) : "memory");
    return v;
}
__device__ __forceinline__ void stg_rlx(void* p, uint4 v) {
    asm volatile("st.relaxed.gpu.global.v4.u32 [%0], {%1,%2,%3,%4};" ::"l"(p), "r"(v.x), "r"(v.y), "r"(v.z), "r"(v.w) : "memory");
}
__device__ __forceinline__ void red_stat(void* p, float s, float q) {
    asm volatile("red.relaxed.gpu.global.add.v4.f32 [%0], {%1,%2,%3,%4};" ::"l"(p), "f"(s), "f"(q), "f"(1.0f), "f"(0.0f) : "memory");
}
__device__ __forceinline__ uint4 lds128(uint32_t a) {
    uint4 v;
    asm volatile("ld.shared.v4.u32 {%0,%1,%2,%3}, [%4];" : "=r"(v.x), "=r"(v.y), "=r"(v.z), "=r"(v.w) : "r"(a) : "memory");
    return v;
}
__device__ __forceinline__ uint4 lds128v(uint32_t a) {
    uint4 v;
    asm volatile("ld.volatile.shared.v4.u32 {%0,%1,%2,%3}, [%4];" : "=r"(v.x), "=r"(v.y), "=r"(v.z), "=r"(v.w) : "r"(a) : "memory");
    return v;
}
__device__ __forceinline__ float2 lds64f(uint32_t a) {
    float2 v;
    asm volatile("ld.shared.v2.f32 {%0,%1}, [%2];" : "=f"(v.x), "=f"(v.y) : "r"(a) : "memory");
    return v;
}
__device__ __forceinline__ float lds32f(uint32_t a) {
    float v;
    asm volatile("ld.shared.f32 %0, [%1];" : "=f"(v) : "r"(a) : "memory");
    return v;
}
__device__ __forceinline__ void sts64f(uint32_t a, float x, float y) {
    asm volatile("st.shared.v2.f32 [%0], {%1,%2};" ::"r"(a), "f"(x), "f"(y) : "memory");
}
__device__ __forceinline__ void stsm4t(uint32_t a, uint32_t r0, uint32_t r1, uint32_t r2, uint32_t r3) {
    asm volatile("stmatrix.sync.aligned.m8n8.x4.trans.shared.b16 [%0], {%1,%2,%3,%4};" ::"r"(a), "r"(r0), "r"(r1), "r"(r2), "r"(r3) : "memory");
}
__device__ __forceinline__ float bf_lo(uint32_t r) { return __uint_as_float(r << 16); }
__device__ __forceinline__ float bf_hi(uint32_t r) { return __uint_as_float(r & 0xffff0000u); }
__device__ __forceinline__ uint32_t pack_bf(float lo, float hi) {
    uint32_t r;
    asm("cvt.rn.bf16x2.f32 %0, %1, %2;" : "=r"(r) : "f"(hi), "f"(lo));
    return r;
}
__device__ __forceinline__ uint32_t ldg_rlx32(const void* p) {
    uint32_t v;
    asm volatile("ld.relaxed.gpu.global.u32 %0, [%1];" : "=r"(v) : "l"(p) : "memory");
    return v;
}
__device__ __forceinline__ void stg_rlx32(void* p, uint32_t v) {
    asm volatile("st.relaxed.gpu.global.u32 [%0], %1;" ::"l"(p), "r"(v) : "memory");
}
__device__ __forceinline__ void reduce_publish(uint32_t red_sm, int lane, void* dst, float e0, float e1, bool one) {
    float s0 = 0.f, q0 = 0.f, s1 = 0.f, q1 = 0.f;
#pragma unroll
    for (int i = 0; i < 4; i++) {
        const uint4 v = lds128(red_sm + lane * 16 + i * 544);
        s0 += __uint_as_float(v.x); q0 += __uint_as_float(v.y);
        s1 += __uint_as_float(v.z); q1 += __uint_as_float(v.w);
    }
    const float t0 = fmaf(64.f, e0, s0), t1 = fmaf(64.f, e1, s1);
    float s = t0 + t1, q = fmaf(e0, s0 + t0, q0) + fmaf(e1, s1 + t1, q1);
#pragma unroll
    for (int o = 1; o < 16; o <<= 1) {
        s += __shfl_xor_sync(~0u, s, o);
        q += __shfl_xor_sync(~0u, q, o);
    }
    if (one) { s += __shfl_xor_sync(~0u, s, 16); q += __shfl_xor_sync(~0u, q, 16); }
    if ((lane & (one ? 31 : 15)) == 0) red_stat(dst, s, q);
    __syncwarp();
}
__device__ __forceinline__ bool mbar_test(uint32_t bar, uint32_t par) {
    uint32_t ok;
    asm volatile("{.reg .pred p; mbarrier.test_wait.parity.shared::cta.b64 p, [%1], %2; selp.u32 %0, 1, 0, p;}"
                 : "=r"(ok) : "r"(bar), "r"(par) : "memory");
    return ok;
}
__device__ __forceinline__ void mbar_wait_t(uint32_t bar, uint32_t par) {
    asm volatile(
        "{\n"
        ".reg .pred p;\n"
        ".reg .u32 n;\n"
        "mov.u32 n, 0;\n"
        "WAIT_LOOP:\n"
        "mbarrier.try_wait.parity.shared::cta.b64 p, [%0], %1;\n"
        "@p bra.uni WAIT_DONE;\n"
        "add.u32 n, n, 1;\n"
        "setp.lt.u32 p, n, 100000;\n"
        "@p bra.uni WAIT_LOOP;\n"
        "trap;\n"
        "WAIT_DONE:\n"
        "}\n" ::"r"(bar), "r"(par) : "memory");
}
__device__ __forceinline__ void arrive_elect(uint32_t bar) {
    asm volatile("{.reg .pred e; elect.sync _|e, 0xffffffff; @e mbarrier.arrive.shared::cta.b64 _, [%0];}" ::"r"(bar) : "memory");
}

struct Params {
    const __nv_bfloat16 *x, *t_emb;
    const __nv_bfloat16* gb[4];
    __nv_bfloat16* out;
    char* h;
    char* box;
    uint4* w2f;
};
__device__ __forceinline__ int acc_off(int half, int b, int grp) { return half * 512 + b * 256 + grp * 128; }
__device__ __forceinline__ int parity_of(uint32_t c0, uint32_t c1, float full) {
    return __uint_as_float(c0) == full && __uint_as_float(c1) != full;
}
__device__ __forceinline__ void bar_n(int id, int n) { asm volatile("bar.sync %0, %1;" ::"r"(id), "r"(n) : "memory"); }

constexpr int SM_E0 = SM_SA, SM_E2 = SM_SA + 32768;
__device__ __noinline__ void aux_part(const Params& p, const CUtensorMap* tme, char* sm, int tid) {
    const int e = blockIdx.x, c4 = tid & 3, er = tid >> 2;
    const uint32_t sb = smem_u32(sm);
    if (tid == 0) {
        const uint32_t bar = sb + SM_MISC + 8 * B_X1;
        mbar_init(bar, 1);
        mbar_expect_tx(bar, 49152);
#pragma unroll
        for (int i = 0; i < 3; i++)
            asm volatile("cp.async.bulk.tensor.2d.shared::cluster.global.mbarrier::complete_tx::bytes [%0], [%1, {%3, %4}], [%2];"
                         ::"r"(sb + (i < 2 ? SM_E0 + i * 16384 : SM_E2)), "l"(tme), "r"(bar), "r"(32 * e), "r"(256 * i) : "memory");
    }
    char* a1 = p.box + acc_off(e & 1, 1, e >> 1);
    const uint32_t c0 = ldg_rlx32(a1 + 8), c1 = ldg_rlx32(a1 + 40);
    uint32_t tv[6];
#pragma unroll
    for (int i = 0; i < 6; i++) tv[i] = __ldg((const uint32_t*)p.t_emb + tid + 128 * i);
    const int par = parity_of(c0, c1, 33.0f);
    float* st_s = (float*)(sm + SM_OP0);
    float* red = st_s + 1536;
#pragma unroll
    for (int i = 0; i < 6; i++) {
        const float lo = bf_lo(tv[i]), hi = bf_hi(tv[i]);
        ((float2*)st_s)[tid + 128 * i] = make_float2(__fdividef(lo, 1.f + __expf(-lo)), __fdividef(hi, 1.f + __expf(-hi)));
    }
    bar_n(2, 128);
    if (tid == 0) red_stat(a1 + 32 * par, 0.f, 0.f);
    mbar_wait(sb + SM_MISC + 8 * B_X1, 0);
    float acc[16];
#pragma unroll
    for (int j = 0; j < 16; j++) acc[j] = 0.f;
#pragma unroll 4
    for (int i = 0; i < 24; i++) {
        const float s0 = st_s[er + 32 * i], s1 = st_s[768 + er + 32 * i];
        const uint4 wv = lds128(sb + (i < 16 ? SM_E0 : SM_E2 - 32768) + tid * 16 + i * 2048);
        const uint32_t r[4] = {wv.x, wv.y, wv.z, wv.w};
#pragma unroll
        for (int j = 0; j < 4; j++) {
            const float lo = bf_lo(r[j]), hi = bf_hi(r[j]);
            acc[2 * j] = fmaf(s0, lo, acc[2 * j]);
            acc[2 * j + 1] = fmaf(s0, hi, acc[2 * j + 1]);
            acc[8 + 2 * j] = fmaf(s1, lo, acc[8 + 2 * j]);
            acc[8 + 2 * j + 1] = fmaf(s1, hi, acc[8 + 2 * j + 1]);
        }
    }
#pragma unroll
    for (int j = 0; j < 16; j++) {
        acc[j] += __shfl_xor_sync(~0u, acc[j], 4);
        acc[j] += __shfl_xor_sync(~0u, acc[j], 8);
        acc[j] += __shfl_xor_sync(~0u, acc[j], 16);
    }
    if ((tid & 31) < 4) {
#pragma unroll
        for (int j = 0; j < 16; j++) red[(tid >> 5) * 64 + (j >> 3) * 32 + c4 * 8 + (j & 7)] = acc[j];
    }
    bar_n(2, 128);
    if (tid < 64) {
        const float s0 = (red[tid] + red[64 + tid]) + (red[128 + tid] + red[192 + tid]);
        const int c = e * 32 + (tid & 31), o = (tid >> 5) * 512;
        const int o2 = 1024 + ((c & ~15) + ((c & 3) << 2) + ((c >> 1) & 2) + ((c >> 3) & 1)) * 4;
        char* eb = p.box + BX_EMB + o;
        stg_rlx32(eb + par * 2048 + c * 4, __float_as_uint(s0) | 1u);
        stg_rlx32(eb + par * 2048 + o2, __float_as_uint(s0) | 1u);
        stg_rlx32(eb + (par ^ 1) * 2048 + c * 4, 0u);
        stg_rlx32(eb + (par ^ 1) * 2048 + o2, 0u);
    }
    bar_n(4, 256);
    if (tid == 64) {
        stg_rlx32(p.box + BX_FLAG + (par ^ 1) * 128 + e * 32, 0u);
        asm volatile("st.release.gpu.global.u32 [%0], %1;" ::"l"(p.box + BX_FLAG + par * 128 + e * 32), "r"(1) : "memory");
    }
}

__device__ __forceinline__ void tma3(uint32_t dst, const CUtensorMap* tm, uint32_t bar, int c1, int c2) {
    asm volatile(
        "cp.async.bulk.tensor.3d.shared::cluster.global.mbarrier::complete_tx::bytes [%0], [%1, {%3, %4, %5}], [%2];"
        ::"r"(dst), "l"(tm), "r"(bar), "r"(0), "r"(c1), "r"(c2) : "memory");
}
__device__ __forceinline__ void prefetch_tm(const CUtensorMap* tm) { asm volatile("prefetch.tensormap [%0];" ::"l"(tm) : "memory"); }
__device__ __forceinline__ uint32_t fmabf2(uint32_t a, uint32_t b, uint32_t c) {
    uint32_t r;
    asm("fma.rn.bf16x2 %0, %1, %2, %3;" : "=r"(r) : "r"(a), "r"(b), "r"(c));
    return r;
}
__device__ __forceinline__ void mma16816(float (&c)[4], const uint4& a, uint32_t b0, uint32_t b1) {
    asm("mma.sync.aligned.m16n8k16.row.col.f32.bf16.bf16.f32 {%0,%1,%2,%3}, {%4,%5,%6,%7}, {%8,%9}, {%0,%1,%2,%3};"
        : "+f"(c[0]), "+f"(c[1]), "+f"(c[2]), "+f"(c[3]) : "r"(a.x), "r"(a.y), "r"(a.z), "r"(a.w), "r"(b0), "r"(b1));
}
__device__ __forceinline__ void mma1688(float (&c)[4], uint32_t a0, uint32_t a1, uint32_t b) {
    asm("mma.sync.aligned.m16n8k8.row.col.f32.bf16.bf16.f32 {%0,%1,%2,%3}, {%4,%5}, {%6}, {%0,%1,%2,%3};"
        : "+f"(c[0]), "+f"(c[1]), "+f"(c[2]), "+f"(c[3]) : "r"(a0), "r"(a1), "r"(b));
}
__device__ __forceinline__ void stat16(const uint4& r0, const uint4& r1, uint32_t dst, int lane) {
    float cs[4] = {0.f, 0.f, 0.f, 0.f}, ca[4] = {0.f, 0.f, 0.f, 0.f}, cb[4] = {0.f, 0.f, 0.f, 0.f};
    mma16816(cs, r0, 0x3e803e80u, 0x3e803e80u);
    mma16816(cs, r1, 0x3e803e80u, 0x3e803e80u);
    mma1688(ca, r0.x, r0.y, r0.x); mma1688(cb, r0.x, r0.y, r0.y);
    mma1688(ca, r0.z, r0.w, r0.z); mma1688(cb, r0.z, r0.w, r0.w);
    mma1688(ca, r1.x, r1.y, r1.x); mma1688(cb, r1.x, r1.y, r1.y);
    mma1688(ca, r1.z, r1.w, r1.z); mma1688(cb, r1.z, r1.w, r1.w);
    const float qd = (lane & 4) ? ca[1] + cb[3] : ca[0] + cb[2];
    sts64f(dst, cs[0] + cs[2], (lane & 3) == (lane >> 3) ? qd : 0.f);
}
__device__ __forceinline__ uint32_t addbf2(uint32_t a, uint32_t b) {
    uint32_t r;
    asm("add.rn.bf16x2 %0, %1, %2;" : "=r"(r) : "r"(a), "r"(b));
    return r;
}
__device__ __forceinline__ uint4 pack_unit(const float (&v)[32], int u) {
    return make_uint4(pack_bf(v[u], v[4 + u]), pack_bf(v[8 + u], v[12 + u]), pack_bf(v[16 + u], v[20 + u]), pack_bf(v[24 + u], v[28 + u]));
}
__device__ __forceinline__ uint4 add_unit(const uint4& a, const uint4& b) {
    return make_uint4(addbf2(a.x, b.x), addbf2(a.y, b.y), addbf2(a.z, b.z), addbf2(a.w, b.w));
}
__device__ __forceinline__ void epi_store(const float (&accF)[32], uint4 (&P)[4], char* dst, uint32_t lo) {
#pragma unroll
    for (int u = 0; u < 4; u++) {
        P[u] = add_unit(pack_unit(accF, u), P[u]);
        P[u].x = max(P[u].x, lo);
        stg_rlx(dst + (u >> 1) * 65536 + (u & 1) * 64, P[u]);
    }
}
__device__ __forceinline__ void epi_stats(const uint4 (&P)[4], uint32_t red_sm) {
    float s[4] = {0.f, 0.f, 0.f, 0.f}, q[4] = {0.f, 0.f, 0.f, 0.f};
#pragma unroll
    for (int u = 0; u < 4; u++) {
        const uint32_t r[4] = {P[u].x, P[u].y, P[u].z, P[u].w};
#pragma unroll
        for (int i = 0; i < 4; i++) {
            const float lo = bf_lo(r[i]), hi = bf_hi(r[i]);
            s[u & 2] += lo; q[u & 2] = fmaf(lo, lo, q[u & 2]);
            s[(u & 2) + 1] += hi; q[(u & 2) + 1] = fmaf(hi, hi, q[(u & 2) + 1]);
        }
    }
    asm volatile("st.shared.v4.f32 [%0], {%1,%2,%3,%4};" ::"r"(red_sm), "f"(s[0] + s[1]), "f"(q[0] + q[1]), "f"(s[2] + s[3]), "f"(q[2] + q[3]) : "memory");
}
__device__ __forceinline__ void send16(uint32_t dst, uint32_t bar, uint32_t a, uint32_t b, uint32_t c, uint32_t d) {
    asm volatile("st.async.weak.shared::cluster.mbarrier::complete_tx::bytes.v4.b32 [%0], {%1,%2,%3,%4}, [%5];"
                 ::"r"(dst), "r"(a), "r"(b), "r"(c), "r"(d), "r"(bar) : "memory");
}

struct Maps { CUtensorMap m[5]; };

__global__ void __cluster_dims__(2, 1, 1) __launch_bounds__(512, 1)
resblock_kernel(const __grid_constant__ Params p, const __grid_constant__ Maps tm) {
    extern __shared__ __align__(1024) char sm[];
    const uint32_t sb = smem_u32(sm), mb = sb + SM_MISC;
    const bool aux = blockIdx.x < 4;
    const int idx = aux ? blockIdx.x : blockIdx.x - 4, k = idx & 1, m = (idx >> 1) & 1, t = idx >> 2, f = k ^ m;
    const int cen = 2 - f;
    const uint32_t seq = f ? 0xc9u : 0x1eu;
    const int tid = threadIdx.x, lane = tid & 31;
    uint4 r0, r1;
    if ((unsigned)(tid - 128) < 256u) {
        r0 = ldg_nc((const char*)p.x + idx * 8192 + (tid - 128) * 16);
        r1 = ldg_nc((const char*)p.x + idx * 8192 + (tid - 128) * 16 + 4096);
    }
    const int wid = __shfl_sync(~0u, tid >> 5, 0);

    if (wid >= 12) {
        asm volatile("setmaxnreg.dec.sync.aligned.u32 64;");
        if (wid == 14) {
            TS(19);
            if (elect_one()) {
#pragma unroll
                for (int j = 0; j < 4; j++) mbar_init(mb + 8 * (B_W + j), 1);
#pragma unroll
                for (int j = 0; j < 4; j++) {
                    mbar_expect_tx(mb + 8 * (B_W + j), WPIECE);
                    tma3(sb + SM_WS + j * WPIECE, &tm.m[2 + aux], mb + 8 * (B_W + j), 64 * m + 16 * j, 9 * k);
                }
            }
            __syncwarp();
            TS2(20);
            asm volatile("bar.arrive 1, 160;" ::: "memory");
            if (aux) return;
            asm volatile("barrier.cluster.arrive.relaxed.aligned;" ::: "memory");
            bar_n(5, 64);
#pragma unroll 1
            for (int j = 0; j < 8; j++) {
                constexpr uint64_t wa = (uint64_t)(B_W + XW0) | (uint64_t)(B_W + 3) << 8 | (uint64_t)B_STAT << 16 | (uint64_t)B_W << 24 |
                                        (uint64_t)(B_ROW + 7) << 32 | (uint64_t)B_W << 40 | (uint64_t)(B_WFREE + 1) << 48 |
                                        (uint64_t)B_W << 56;
                mbar_wait(mb + 8 * (uint32_t)((wa >> (8 * j)) & 63), 0);
                if (j >= 4) {
                    mbar_wait(mb + 8 * (B_FREE - 2 + (j >> 1)), 0);
                    for (const uint32_t c0 = clock32(); clock32() - c0 < ((j & 1) ? HDELAY2 : HDELAY);) __nanosleep(32);
                }
                const uint32_t dst = sb + (j < 4 ? SM_SA + j * 16384 : (j < 6 ? SM_SB : SM_WS) + (j & 1) * 16384);
                const int plane = (j & 2) * 64 + 64 * k + (j < 4 ? 0 : __float_as_uint(lds32f(sb + SM_PAR)) * 256);
                const uint32_t bar = mb + 8 * (B_S + j), rs = seq >> (4 * (j & 1));
                if (elect_one()) {
                    mbar_expect_tx(bar, 16384);
                    tma3(dst, &tm.m[j >> 2], bar, plane, 2 * t - 1 + (rs & 3));
                    tma3(dst + 8192, &tm.m[j >> 2], bar, plane, 2 * t - 1 + ((rs >> 2) & 3));
                }
                __syncwarp();
                TS2(j);
            }
            TS_DUMP();
            return;
        }
        if (aux) return;
        if (wid == 12) {
            const uint32_t oline = acc_off(idx >> 6, 0, (idx >> 5) & 1);
            const uint32_t c0 = ldg_rlx32(p.box + oline + 8), c1 = ldg_rlx32(p.box + oline + 40);
            uint32_t gb[4];
#pragma unroll
            for (int j = 0; j < 4; j++) asm volatile("ld.global.nc.u32 %0, [%1];" : "=r"(gb[j]) : "l"(p.gb[j] + 64 * k + 2 * lane));
            const int par = parity_of(c0, c1, 32.0f);
            asm volatile("st.shared.u32 [%0], %1;" ::"r"(sb + SM_PAR), "r"(par) : "memory");
            asm volatile("st.shared.v4.u32 [%0], {%1,%1,%1,%1};" ::"r"(sb + SM_COEF + 2048 + lane * 16), "r"(0) : "memory");
            asm volatile("barrier.cluster.arrive.relaxed.aligned;" ::: "memory");
            const uint32_t gl = (lane & 16) * 8 + par * 32;
#pragma unroll 1
            for (int gi = 0; gi < 4; gi++) {
                const int isH = gi >> 1;
                char* const bx = p.box + (gi & 1) * 256 + isH * 16;
                char* pub = bx + (isH ? m * 512 + gl : oline + par * 32);
                char* src = bx + k * 512 + gl;
                asm volatile("" : "+l"(pub), "+l"(src));
                uint2 eo = make_uint2(0, 0), ei = eo;
                if (isH) {
                    const char* eb = p.box + BX_EMB + par * 2048 + (gi & 1) * 512 + lane * 8;
                    int it = 0;
                    do {
                        asm volatile("ld.relaxed.gpu.global.v2.u32 {%0,%1}, [%2];" : "=r"(eo.x), "=r"(eo.y) : "l"(eb + 1024 + m * 256) : "memory");
                        asm volatile("ld.relaxed.gpu.global.v2.u32 {%0,%1}, [%2];" : "=r"(ei.x), "=r"(ei.y) : "l"(eb + k * 256) : "memory");
                    } while (__any_sync(~0u, min(min(eo.x, eo.y), min(ei.x, ei.y)) == 0u) && ++it < SPIN_LIMIT);
                    gb[0] = gb[2]; gb[1] = gb[3];
                    mbar_wait(mb + 8 * (B_FREE - 2 + gi), 0);
                } else {
                    bar_n(3 + gi, gi ? 288 : 352);
                }
                reduce_publish(sb + SM_RED + (gi == 1) * 2176, lane, pub, __uint_as_float(eo.x),
                               __uint_as_float(eo.y), !isH);
                if (gi == 0) asm volatile("bar.arrive 6, 160;" ::: "memory");
                TS(4 + gi * 2);
                const uint32_t want = isH ? 0x42800000u : 0x42000000u + gi * 0x40000u;
                uint4 v = make_uint4(0, 0, want, 0);
                int it = 0;
                do {
                    if ((lane & 15) == 0) v = ldg_rlx(src);
                } while (__any_sync(~0u, v.z != want) && ++it < SPIN_LIMIT);
                const float mean = __shfl_sync(~0u, __uint_as_float(v.x), lane & 16) * (1.0f / 131072.0f);
                const float msq = __shfl_sync(~0u, __uint_as_float(v.y), lane & 16) * (4.0f / 131072.0f);
                float rs;
                asm("rsqrt.approx.ftz.f32 %0, %1;" : "=f"(rs) : "f"(fmaxf(fmaf(-4.0f * mean, mean, msq), 0.f) + 4e-5f));
                const float a0 = rs * bf_lo(gb[0]), a1 = rs * bf_hi(gb[0]);
                const uint32_t ca0 = pack_bf(a0, a0), ca1 = pack_bf(a1, a1);
                const float b0 = fmaf(__uint_as_float(ei.x) - mean, bf_hi(ca0), 0.5f * bf_lo(gb[1]));
                const float b1 = fmaf(__uint_as_float(ei.y) - mean, bf_hi(ca1), 0.5f * bf_hi(gb[1]));
                asm volatile("st.shared.v4.u32 [%0], {%1,%2,%3,%4};" ::"r"(sb + SM_COEF + gi * 512 + lane * 16), "r"(ca0), "r"(pack_bf(b0, b0)),
                             "r"(ca1), "r"(pack_bf(b1, b1)) : "memory");
                __syncwarp();
                arrive_elect(mb + 8 * (B_STAT + gi));
                if ((idx | (lane & 15)) < 2 && (lane & 1) == 0) stg_rlx(bx + k * 512 + (gl ^ 32), make_uint4(0, 0, 0, 0));
                __syncwarp();
                TS(5 + gi * 2);
            }
        } else if (wid == 13) {
            if (elect_one()) {
                prefetch_tm(&tm.m[0]);
#pragma unroll
                for (int j = 0; j < B_W; j++) mbar_init(mb + 8 * j, j < B_FREE ? 8 : (j < B_P ? 4 : 1));
#pragma unroll
                for (int j = 0; j < 4; j++) mbar_expect_tx(mb + 8 * (B_P + j), 8192);
                asm volatile("fence.mbarrier_init.release.cluster;" ::: "memory");
            }
            __syncwarp();
            TS2(20);
            asm volatile("bar.arrive 5, 64;" ::: "memory");
            asm volatile("bar.arrive 3, 352;" ::: "memory");
            asm volatile("barrier.cluster.arrive.relaxed.aligned;" ::: "memory");
            asm volatile("barrier.cluster.wait.aligned;" ::: "memory");
            uint32_t rbar;
            asm("mapa.shared::cluster.u32 %0, %1, %2;" : "=r"(rbar) : "r"(mb + 8 * B_SAFREE), "r"(k ^ 1));
#pragma unroll 1
            for (int j = 0; j < 16; j++) {
                const int o = (j & 7) * 8;
                mbar_wait(mb + 8 * B_ROWA + o, j >> 3);
                asm volatile(
                    "{\n"
                    ".reg .pred e, r;\n"
                    "fence.proxy.async.shared::cta;\n"
                    "elect.sync _|e, 0xffffffff;\n"
                    "@e mbarrier.arrive.shared::cta.b64 _, [%0];\n"
                    "setp.eq.and.u32 r, %2, 1, e;\n"
                    "@r mbarrier.arrive.relaxed.cluster.shared::cluster.b64 _, [%1];\n"
                    "}\n" ::"r"(mb + 8 * B_ROW + o), "r"(rbar), "r"(j) : "memory");
                TS2(j);
            }
        } else {
            asm volatile("barrier.cluster.arrive.relaxed.aligned;" ::: "memory");
            bar_n(3, 352);
            if (elect_one()) {
                asm volatile("cp.async.bulk.prefetch.L2.global [%0], 8192;" ::"l"((const char*)p.x + (128 + idx) * 8192) : "memory");
                prefetch_tm(&tm.m[1]);
            }
            const int par = __float_as_uint(lds32f(sb + SM_PAR));
            mbar_wait(mb + 8 * B_WFREE, 0);
            mbar_wait(mb + 8 * (B_STAT + 1), 0);
            uint32_t fl;
            int it = 0;
            do {
                asm volatile("ld.acquire.gpu.global.u32 %0, [%1];" : "=r"(fl) : "l"(p.box + BX_FLAG + par * 128 + (idx & 3) * 32) : "memory");
            } while (__any_sync(~0u, fl == 0) && ++it < SPIN_LIMIT);
            asm volatile("fence.proxy.async.global;" ::: "memory");
            if (elect_one()) {
                mbar_expect_tx(mb + 8 * B_W2, WSZ);
                asm volatile("cp.async.bulk.shared::cluster.global.mbarrier::complete_tx::bytes [%0], [%1], %2, [%3];"
                             ::"r"(sb + SM_WS), "l"(p.w2f + (idx & 3) * 4608), "r"(WSZ), "r"(mb + 8 * B_W2) : "memory");
            }
            mbar_wait(mb + 8 * (B_STAT + 2), 0);
            if (elect_one()) {
                mbar_expect_tx(mb + 8 * B_RES, 16384);
                tma3(sb + SM_SA + 16384, &tm.m[0], mb + 8 * B_RES, 64 * m, 2 * t + 1 - f);
                tma3(sb + SM_SA + 24576, &tm.m[0], mb + 8 * B_RES, 128 + 64 * m, 2 * t + 1 - f);
            }
            mbar_wait(mb + 8 * (B_STAT + 3), 0);
            uint4* oh = (uint4*)(p.h + (par ^ 1) * (2 << 20)) + idx * 1024 + lane;
#pragma unroll 1
            for (int u = 0; u < 32; u++) oh[u * 32] = make_uint4(0, 0, 0, 0);
        }
    } else if (wid >= 4) {
        const int ht = tid - 128, hw = wid - 4;
        if (aux) {
            asm volatile("setmaxnreg.dec.sync.aligned.u32 96;");
            if (hw < 4) aux_part(p, &tm.m[4], sm, ht);
            TS(0); TS_DUMP();
            return;
        }
        asm volatile("barrier.cluster.arrive.relaxed.aligned;" ::: "memory");
        TS2(1);
        stat16(r0, r1, sb + SM_RED + ht * 8 + (ht >> 6) * 32, lane);
        TS2(2);
        asm volatile("setmaxnreg.dec.sync.aligned.u32 96;");
        bar_n(3, 352);
        for (const uint32_t c0 = clock32(); clock32() - c0 < XDELAY;) __nanosleep(32);
        TS2(3);
        stat16(ldg_rlx((const char*)p.x + (128 + idx) * 8192 + ht * 16), ldg_rlx((const char*)p.x + (128 + idx) * 8192 + 4096 + ht * 16),
               sb + SM_RED + 2176 + ht * 8 + (ht >> 6) * 32, lane);
        asm volatile("bar.arrive 4, 288;" ::: "memory");
        TS2(20);
        const int icl = (hw & 4) * 8 + (lane & 28) + (hw & 3);
        const uint32_t st_lane = hw * CHUNK + (2 * (lane >> 3) + (lane & 1) + 1) * PLANE + ((lane >> 1) & 3) * 32;
        uint32_t dup_lane, dup_mul = 1;
        {
            const int bd = ((lane >> 1) & 7) + ((lane & 1) ? 1 : -1);
            dup_lane = hw * CHUNK + ((lane & 1) ? 0 : 9 * PLANE) + (2 * (bd & 3) + ((bd >> 2) & 1)) * 16;
            if (bd < 0 || bd > 7) { dup_lane = sb + SM_OP0 + 512; dup_mul = 0; }
        }
        const uint32_t ld_lane = icl * 128 + (((lane & 3) ^ (icl & 7)) << 4);
        const int inv = t == 0 ? 3 - f : (t == 31 ? 1 + 2 * f : 4);
        uint4 x0, x1;
        float2 cf;
        uint32_t stage = sb + SM_SA, coef = sb + SM_COEF;
        bool have = false;
#pragma unroll 1
        for (int j = 0; j < 16; j++) {
            const int orow = (seq >> (2 * (j & 3))) & 3;
            if (!have) {
                mbar_wait(mb + 8 * (B_S + (j >> 1)), 0);
                x0 = lds128(stage + ld_lane);
                x1 = lds128(stage + (ld_lane ^ 64));
#pragma unroll 1
                for (int it = 0; j >= 8 && (j & 3) != inv && __any_sync(~0u, min(x0.x, x1.x) == 0u) && it < SPIN_LIMIT; it++) {
                    const char* src = p.h + (__float_as_uint(lds32f(sb + SM_PAR)) * 2 + ((j >> 2) & 1)) * (1 << 20) +
                                      ((64 * k + icl) * 64 + 2 * t - 1 + orow) * 128 + (lane & 3) * 16;
                    x0 = ldg_rlx(src);
                    x1 = ldg_rlx(src + 64);
                }
                mbar_wait(mb + 8 * (B_STAT + (j >> 2)), 0);
                cf = lds64f(coef + icl * 8);
            }
            const uint32_t ca = __float_as_uint(cf.x), cb = __float_as_uint(cf.y);
            uint32_t h[8] = {fmabf2(x0.x, ca, cb), fmabf2(x0.y, ca, cb), fmabf2(x0.z, ca, cb), fmabf2(x0.w, ca, cb),
                             fmabf2(x1.x, ca, cb), fmabf2(x1.y, ca, cb), fmabf2(x1.z, ca, cb), fmabf2(x1.w, ca, cb)};
            stage += j == 7 ? -24576 : (j == 11 ? SM_WS - SM_SB - 24576 : 8192);
            coef = sb + SM_COEF + (((j + 1) & 3) == inv ? 4 : (j + 1) >> 2) * 512;
            const bool nx = mbar_test(mb + 8 * (B_S + ((j + 1) >> 1)), 0), ns = mbar_test(mb + 8 * (B_STAT + ((j + 1) >> 2)), 0);
            x0 = lds128v(stage + ld_lane);
            x1 = lds128v(stage + (ld_lane ^ 64));
            cf = lds64f(coef + icl * 8);
            const uint32_t u0 = sb + SM_OP0 - (j & 4) * (OPSZ / 4) + orow * 128;
#pragma unroll
            for (int i = 0; i < 8; i++) {
                uint32_t th;
                asm("tanh.approx.bf16x2 %0, %1;" : "=r"(th) : "r"(h[i]));
                h[i] = fmabf2(h[i], th, h[i]);
            }
            stsm4t(u0 + st_lane, h[0], h[1], h[2], h[3]);
            stsm4t(u0 + st_lane + 16, h[4], h[5], h[6], h[7]);
            asm volatile("stmatrix.sync.aligned.m8n8.x2.trans.shared.b16 [%0], {%1,%2};"
                         ::"r"(u0 * dup_mul + dup_lane), "r"(__byte_perm(h[0], h[3], 0x7610)), "r"(__byte_perm(h[4], h[7], 0x7610)) : "memory");
            arrive_elect(mb + 8 * (B_ROWA + (j & 7)));
            TS(4 + j);
            have = __all_sync(~0u, nx && ns && min(x0.x, x1.x) != 0u);
        }
    } else {
        const uint32_t t16 = tid * 16;
        if (!aux) {
            const uint32_t a = sb + SM_OP1 + (tid >> 3) * CHUNK + ((tid >> 1) & 3) * 128 + ((tid & 1) ? 9 * PLANE + 7 * 16 : 0);
            asm volatile("st.shared.v4.u32 [%0], {%1,%1,%1,%1};" ::"r"(a), "r"(0) : "memory");
            asm volatile("fence.proxy.async.shared::cta;" ::: "memory");
            asm volatile("barrier.cluster.arrive.relaxed.aligned;" ::: "memory");
        }
        bar_n(1, 160);
        if (!aux) bar_n(6, 160);
        asm volatile("setmaxnreg.inc.sync.aligned.u32 256;");
        uint32_t W[144];
        {
            const int q = lane & 3, rr = (lane >> 3) + (lane & 4);
            const uint32_t wsrc = sb + SM_WS + wid * WPIECE + q * 2048 + rr * 128;
            mbar_wait(mb + 8 * (B_W + wid), 0);
            TS2(3);
#pragma unroll
            for (int blk = 0; blk < 2; blk++)
#pragma unroll
                for (int hh = 0; hh < 2; hh++) {
                    uint32_t seg[36];
#pragma unroll
                    for (int i = 0; i < 9; i++) {
                        const int z = (q + i + 4 * blk) * 16;
                        const uint4 v = lds128(wsrc + ((z ^ (rr << 4)) & 0x70) + ((z & 0x80) << 4) + blk * 8192 + hh * 1024);
                        seg[4 * i] = v.x; seg[4 * i + 1] = v.y; seg[4 * i + 2] = v.z; seg[4 * i + 3] = v.w;
                    }
#pragma unroll
                    for (int j = 0; j < 4; j++)
#pragma unroll
                        for (int tap = 0; tap < 9; tap++) {
                            const int el = 9 * j + tap;
                            W[((2 * blk + (j >> 1)) * 9 + tap) * 4 + (j & 1) * 2 + hh] =
                                __byte_perm(seg[el >> 1], seg[(el >> 1) + 18], (el & 1) ? 0x7632 : 0x5410);
                        }
                }
        }
        if (__builtin_expect(aux, 0)) {
#pragma unroll
            for (int i = 0; i < 36; i++) p.w2f[idx * 4608 + i * 128 + tid] = make_uint4(W[4 * i], W[4 * i + 1], W[4 * i + 2], W[4 * i + 3]);
            asm volatile("bar.arrive 4, 256;" ::: "memory");
            return;
        }
        arrive_elect(mb + 8 * B_WFREE);
        const int par = __shfl_sync(~0u, __float_as_uint(lds32f(sb + SM_PAR)), 0);
        float accS[32], accF[32];
        uint4 P[4];
        const uint32_t out_off = ((64 * m + 16 * wid + (lane >> 3) + (lane & 4)) * 64 + 2 * t + f) * 128 + (lane & 3) * 16;
        uint32_t rsb;
        asm("mapa.shared::cluster.u32 %0, %1, %2;" : "=r"(rsb) : "r"(sb), "r"(k ^ 1));
        const uint64_t dconst = ((uint64_t)(CHUNK / 16) << 16) | ((uint64_t)(PLANE / 16) << 32);
        TS2(4);
#pragma unroll
        for (int i = 0; i < 32; i++) { accF[i] = 0.f; accS[i] = 0.f; }
        const uint32_t d0 = (((sb + SM_OP0) & 0x3ffff) >> 4) + cen * 8;
        const uint32_t raddr = sb + SM_RED + (tid & 3) * 544 + (tid >> 2) * 16;
        const uint32_t xaddr = sb + SM_SA + 16384 + ((out_off >> 6) & 0x1f80) + ((out_off ^ (out_off >> 9)) & 0x70);
#pragma unroll 1
        for (int ph = 0;; ph++) {
            const int cv = ph >= 3, b = ph - 3 * cv, it = 2 * cv + b;
            const uint32_t rb = mb + 8 * B_ROW + b * 32;
            const uint64_t dS = dconst | (uint64_t)(d0 - b * (OPSZ / 16));
            const uint64_t dF = dS + (uint64_t)(int64_t)(16 * f - 8);
            if (b < 2) {
                mbar_wait_t(rb, cv);
                TS(8 + 4 * it);
                wg_fence();
                mma_sub<0>(accS, W, dS);
                mma_sub<1>(accS, W, dS);
            }
            mbar_wait_t(mb + 8 * (B_P - 1 + it), ph == 0);
#pragma unroll
            for (int u = 0; u < 4; u++) P[u] = lds128v(sb + SM_SA + (b >> 1) * 8192 + u * 2048 + t16);
            if (b < 2) {
                wg_fence();
                mma_sub<2>(accS, W, dS);
                mma_sub<3>(accS, W, dS);
                wg_commit();
                wg_wait<1>();
            } else {
                wg_wait<0>();
            }
            if (b) {
                TS3(2);
                acc_fence(accF);
                epi_store(accF, P, (cv ? (char*)p.out : p.h + par * (2 << 20)) + (b - 1) * (1 << 20) + out_off, cv ^ 1);
                TS3(5);
                if (ph == 5) { wg_wait<0>(); break; }
                if (cv == 0) {
                    epi_stats(P, raddr);
                    __syncwarp();
                    arrive_elect(mb + 8 * (B_FREE - 1 + b));
                    TS2(9 + 4 * it);
                }
                if (b == 2) {
                    mbar_wait_t(mb + 8 * B_W2, 0);
#pragma unroll
                    for (int i = 0; i < 36; i++) {
                        const uint4 v = lds128(sb + SM_WS + i * 2048 + t16);
                        W[4 * i] = v.x; W[4 * i + 1] = v.y; W[4 * i + 2] = v.z; W[4 * i + 3] = v.w;
                    }
                    arrive_elect(mb + 8 * (B_WFREE + 1));
                    continue;
                }
            }
            mbar_wait_t(rb + 8, cv);
            wg_fence();
            mma_sub<4>(accS, W, dS);
            mma_sub<5>(accS, W, dS);
            mma_sub<6>(accS, W, dS);
            mma_sub<7>(accS, W, dS);
            mbar_wait_t(rb + 16, cv);
            TS3(7);
            wg_fence();
            mma_sub<8>(accS, W, dS);
            mma_sub<9>(accS, W, dS);
            mma_sub<10>(accS, W, dS);
            mma_sub<11>(accS, W, dS);
            wg_commit();
            TS2(10 + 4 * it);
            mbar_wait_t(mb + 8 * (cv ? B_RES : B_SAFREE), 0);
#pragma unroll
            for (int u = 0; u < 4; u++) P[u] = lds128v(((xaddr + b * 8192) ^ ((u & 1) * 64)) + (u >> 1) * 1024);
            wg_fence();
            mma_sub<0>(accF, W, dF);
            mma_sub<1>(accF, W, dF);
            mma_sub<2>(accF, W, dF);
            wg_commit();
            TS3(24);
            wg_wait<1>();
            acc_fence(accS);
            TS3(25);
            {
                uint4 o[4];
#pragma unroll
                for (int u = 0; u < 4; u++) o[u] = pack_unit(accS, u);
                if (cv) {
#pragma unroll
                    for (int u = 0; u < 4; u++) o[u] = add_unit(o[u], P[u]);
                }
#pragma unroll
                for (int u = 0; u < 4; u++)
                    send16(rsb + SM_SA + b * 8192 + u * 2048 + t16, rsb + SM_MISC + 8 * (B_P + it), o[u].x, o[u].y, o[u].z, o[u].w);
            }
            wg_fence();
            TS3(26);
            mma_sub<3>(accF, W, dF);
            mbar_wait_t(rb + 24, cv);
            wg_fence();
            mma_sub<4>(accF, W, dF);
            mma_sub<5>(accF, W, dF);
            mma_sub<6>(accF, W, dF);
            mma_sub<7>(accF, W, dF);
            mma_sub<8>(accF, W, dF);
            mma_sub<9>(accF, W, dF);
            mma_sub<10>(accF, W, dF);
            mma_sub<11>(accF, W, dF);
            wg_commit();
            TS2(11 + 4 * it);
        }
    }
    TS(0);
    TS_DUMP();
}

typedef CUresult (*EncodeFn)(CUtensorMap*, CUtensorMapDataType, cuuint32_t, void*, const cuuint64_t*, const cuuint64_t*,
                             const cuuint32_t*, const cuuint32_t*, CUtensorMapInterleave, CUtensorMapSwizzle,
                             CUtensorMapL2promotion, CUtensorMapFloatOOBfill);

void make_wmap(EncodeFn enc, CUtensorMap* tm, void* w) {
    cuuint64_t gd[3] = {64, 128, 18};
    cuuint64_t gs[2] = {2304, 128};
    cuuint32_t bd[3] = {64, 16, 9};
    cuuint32_t es[3] = {1, 1, 1};
    enc(tm, CU_TENSOR_MAP_DATA_TYPE_BFLOAT16, 3, w, gd, gs, bd, es, CU_TENSOR_MAP_INTERLEAVE_NONE,
        CU_TENSOR_MAP_SWIZZLE_128B, CU_TENSOR_MAP_L2_PROMOTION_L2_128B, CU_TENSOR_MAP_FLOAT_OOB_FILL_NONE);
}

void make_amap(EncodeFn enc, CUtensorMap* tm, void* a, int planes, int rows) {
    cuuint64_t gd[3] = {64, (cuuint64_t)planes, 64};
    cuuint64_t gs[2] = {8192, 128};
    cuuint32_t bd[3] = {64, 64, (cuuint32_t)rows};
    cuuint32_t es[3] = {1, 1, 1};
    enc(tm, CU_TENSOR_MAP_DATA_TYPE_BFLOAT16, 3, a, gd, gs, bd, es, CU_TENSOR_MAP_INTERLEAVE_NONE,
        CU_TENSOR_MAP_SWIZZLE_128B, CU_TENSOR_MAP_L2_PROMOTION_L2_128B, CU_TENSOR_MAP_FLOAT_OOB_FILL_NONE);
}

}

extern "C" void kernel_launch(void* const* d_in, const int* in_sizes, int n_in, void* d_out, int out_size) {
    static EncodeFn enc = nullptr;
    static void *ph, *pbox, *pw2f;
    if (!enc) {
        cudaGetSymbolAddress(&ph, g_h);
        cudaGetSymbolAddress(&pbox, g_box);
        cudaGetSymbolAddress(&pw2f, g_w2f);
        void* fn = nullptr;
        cudaDriverEntryPointQueryResult qr;
        cudaGetDriverEntryPoint("cuTensorMapEncodeTiled", &fn, cudaEnableDefault, &qr);
        enc = (EncodeFn)fn;
        cudaFuncSetAttribute(resblock_kernel, cudaFuncAttributeMaxDynamicSharedMemorySize, SMEM_BYTES);
    }
    Params p;
    p.x = (const __nv_bfloat16*)d_in[0];
    p.t_emb = (const __nv_bfloat16*)d_in[1];
    p.gb[0] = (const __nv_bfloat16*)d_in[2];
    p.gb[1] = (const __nv_bfloat16*)d_in[3];
    p.gb[2] = (const __nv_bfloat16*)d_in[6];
    p.gb[3] = (const __nv_bfloat16*)d_in[7];
    p.out = (__nv_bfloat16*)d_out;
    p.h = (char*)ph;
    p.box = (char*)pbox;
    p.w2f = (uint4*)pw2f;
    Maps tm;
    {
        cuuint64_t gd[2] = {128, 768};
        cuuint64_t gs[1] = {256};
        cuuint32_t bd[2] = {32, 256};
        cuuint32_t es[2] = {1, 1};
        enc(&tm.m[4], CU_TENSOR_MAP_DATA_TYPE_BFLOAT16, 2, d_in[5], gd, gs, bd, es, CU_TENSOR_MAP_INTERLEAVE_NONE,
            CU_TENSOR_MAP_SWIZZLE_NONE, CU_TENSOR_MAP_L2_PROMOTION_NONE, CU_TENSOR_MAP_FLOAT_OOB_FILL_NONE);
    }
    make_amap(enc, &tm.m[0], d_in[0], 256, 1);
    make_amap(enc, &tm.m[1], ph, 512, 1);
    make_wmap(enc, &tm.m[2], d_in[4]);
    make_wmap(enc, &tm.m[3], d_in[8]);
    resblock_kernel<<<132, 512, SMEM_BYTES>>>(p, tm);
}
```

```cpp
#include <cuda_runtime.h>
#include <cuda_bf16.h>
#include <cuda.h>
#include <stdint.h>

namespace {

constexpr int PLANE = 528;
constexpr int CHUNK = 10 * PLANE;
constexpr int OPSZ = 8 * CHUNK;
constexpr int WPIECE = 18432;
constexpr int WSZ = 4 * WPIECE;
constexpr int SM_WS = 0;
constexpr int SM_SA = WSZ;
constexpr int SM_SB = SM_SA + 32768;
constexpr int SM_OP1 = SM_SB + 32768;
constexpr int SM_OP0 = SM_OP1 + OPSZ;
constexpr int SM_MISC = SM_OP0 + OPSZ;
constexpr int B_ROWA = 0;
constexpr int B_FREE = 9;
constexpr int B_WFREE = 11;
constexpr int B_P = 13;
constexpr int B_ROW = 17;
constexpr int B_SAFREE = 26;
constexpr int B_RES = 27;
constexpr int B_X1 = 29;
constexpr int B_S = 30;
constexpr int B_STAT = 38;
constexpr int B_W = 42;
constexpr int SM_PAR = SM_MISC + 448;
constexpr int SM_COEF = SM_MISC + 512;
constexpr int SM_RED = SM_COEF + 2560;
constexpr int SM_EMB = SM_RED + 2048;
constexpr int SM_TS = SM_EMB + 2048;
constexpr int SMEM_BYTES = SM_TS;
#define TIT 1
#define HDELAY2 100
#define P1STAT 0
#define XMODE 0
#define PDELAY 350
#define NSPLIT 9
#define HOLD 1
#define XD 500
#define EROW 1
#define PT0 2250
#define PSYNC 0
#define XW0 0
#define HDELAY 400
constexpr int SPIN_LIMIT = 200000;

__device__ uint4 g_h[2 * 2 * 128 * 64 * 8];
__device__ __align__(128) uint4 g_box[192];
constexpr int BX_EMB = 1024;
#define TS3(id) do { } while (0)
#define TS2(id) do { } while (0)
#define TS(id) do { } while (0)
#define TS_DUMP() do { } while (0)

__device__ __forceinline__ uint32_t smem_u32(const void* p) { return (uint32_t)__cvta_generic_to_shared(p); }
__device__ __forceinline__ void mbar_init(uint32_t bar, int cnt) {
    asm volatile("mbarrier.init.shared::cta.b64 [%0], %1;" ::"r"(bar), "r"(cnt) : "memory");
}
__device__ __forceinline__ void mbar_expect_tx(uint32_t bar, uint32_t bytes) {
    asm volatile("mbarrier.arrive.expect_tx.shared::cta.b64 _, [%0], %1;" ::"r"(bar), "r"(bytes) : "memory");
}
__device__ __forceinline__ void mbar_wait(uint32_t bar, uint32_t par) {
    asm volatile(
        "{\n"
        ".reg .pred p;\n"
        ".reg .u32 n;\n"
        "mov.u32 n, 0;\n"
        "WAIT_LOOP:\n"
        "mbarrier.try_wait.parity.shared::cta.b64 p, [%0], %1;\n"
        "add.u32 n, n, 1;\n"
        "setp.lt.and.u32 p, n, 100000, !p;\n"
        "@p bra.uni WAIT_LOOP;\n"
        "}\n" ::"r"(bar), "r"(par) : "memory");
}
__device__ __forceinline__ uint32_t clock32() {
    uint32_t c;
    asm volatile("mov.u32 %0, %%clock;" : "=r"(c));
    return c;
}
__device__ __forceinline__ bool elect_one() {
    uint32_t r;
    asm volatile("{.reg .pred p; elect.sync _|p, 0xffffffff; selp.u32 %0, 1, 0, p;}" : "=r"(r));
    return r;
}
__device__ __forceinline__ void wg_fence() { asm volatile("wgmma.fence.sync.aligned;" ::: "memory"); }
__device__ __forceinline__ void wg_commit() { asm volatile("wgmma.commit_group.sync.aligned;" ::: "memory"); }
template <int N> __device__ __forceinline__ void wg_wait() {
    asm volatile("wgmma.wait_group.sync.aligned %0;" ::"n"(N) : "memory");
}
__device__ __forceinline__ void wgmma_acc(float (&d)[32], const uint32_t* a, uint64_t desc) {
    asm volatile(
        "wgmma.mma_async.sync.aligned.m64n64k16.f32.bf16.bf16 "
        "{%0,%1,%2,%3,%4,%5,%6,%7,%8,%9,%10,%11,%12,%13,%14,%15,%16,%17,%18,%19,%20,%21,%22,%23,%24,%25,%26,%27,%28,%29,%30,%31}, "
        "{%32,%33,%34,%35}, %36, 1, 1, 1, 0;\n"
        : "+f"(d[0]), "+f"(d[1]), "+f"(d[2]), "+f"(d[3]), "+f"(d[4]), "+f"(d[5]), "+f"(d[6]), "+f"(d[7]), "+f"(d[8]), "+f"(d[9]), "+f"(d[10]), "+f"(d[11]), "+f"(d[12]), "+f"(d[13]), "+f"(d[14]), "+f"(d[15]), "+f"(d[16]), "+f"(d[17]), "+f"(d[18]), "+f"(d[19]), "+f"(d[20]), "+f"(d[21]), "+f"(d[22]), "+f"(d[23]), "+f"(d[24]), "+f"(d[25]), "+f"(d[26]), "+f"(d[27]), "+f"(d[28]), "+f"(d[29]), "+f"(d[30]), "+f"(d[31])
        : "r"(a[0]), "r"(a[1]), "r"(a[2]), "r"(a[3]), "l"(desc));
}
__device__ __forceinline__ void wgmma_first(float (&d)[32], const uint32_t* a, uint64_t desc) {
    asm volatile(
        "wgmma.mma_async.sync.aligned.m64n64k16.f32.bf16.bf16 "
        "{%0,%1,%2,%3,%4,%5,%6,%7,%8,%9,%10,%11,%12,%13,%14,%15,%16,%17,%18,%19,%20,%21,%22,%23,%24,%25,%26,%27,%28,%29,%30,%31}, "
        "{%32,%33,%34,%35}, %36, 0, 1, 1, 0;\n"
        : "=f"(d[0]), "=f"(d[1]), "=f"(d[2]), "=f"(d[3]), "=f"(d[4]), "=f"(d[5]), "=f"(d[6]), "=f"(d[7]), "=f"(d[8]), "=f"(d[9]), "=f"(d[10]), "=f"(d[11]), "=f"(d[12]), "=f"(d[13]), "=f"(d[14]), "=f"(d[15]), "=f"(d[16]), "=f"(d[17]), "=f"(d[18]), "=f"(d[19]), "=f"(d[20]), "=f"(d[21]), "=f"(d[22]), "=f"(d[23]), "=f"(d[24]), "=f"(d[25]), "=f"(d[26]), "=f"(d[27]), "=f"(d[28]), "=f"(d[29]), "=f"(d[30]), "=f"(d[31])
        : "r"(a[0]), "r"(a[1]), "r"(a[2]), "r"(a[3]), "l"(desc));
}
__device__ __forceinline__ void acc_fence(float (&d)[32]) {
#pragma unroll
    for (int i = 0; i < 32; i++) asm volatile("" : "+f"(d[i])::"memory");
}
template <int SUB>
__device__ __forceinline__ void mma_sub(float (&acc)[32], const uint32_t (&W)[144], uint64_t dcen) {
    constexpr int RG = SUB / 4, KS = SUB % 4;
    constexpr int TI = RG == 0 ? 1 : (RG == 1 ? 2 : 0);
    constexpr int ROFF = (TI - 1) * 8;
#pragma unroll
    for (int dx = 0; dx < 3; dx++) {
        uint64_t d = dcen + (uint64_t)(int64_t)(KS * (2 * CHUNK / 16) + dx * (PLANE / 16) + ROFF);
        if (SUB == 0 && dx == 0) wgmma_first(acc, &W[(KS * 9 + TI * 3 + dx) * 4], d);
        else wgmma_acc(acc, &W[(KS * 9 + TI * 3 + dx) * 4], d);
    }
}
__device__ __forceinline__ uint4 ldg_nc(const void* p) {
    uint4 v;
    asm volatile("ld.global.nc.L1::no_allocate.v4.u32 {%0,%1,%2,%3}, [%4];"
                 : "=r"(v.x), "=r"(v.y), "=r"(v.z), "=r"(v.w) : "l"(p));
    return v;
}
__device__ __forceinline__ uint4 ldg_rlx(const void* p) {
    uint4 v;
    asm volatile("ld.relaxed.gpu.global.v4.u32 {%0,%1,%2,%3}, [%4];"
                 : "=r"(v.x), "=r"(v.y), "=r"(v.z), "=r"(v.w) : "l"(p) : "memory");
    return v;
}
__device__ __forceinline__ void stg_rlx(void* p, uint4 v) {
    asm volatile("st.relaxed.gpu.global.v4.u32 [%0], {%1,%2,%3,%4};" ::"l"(p), "r"(v.x), "r"(v.y), "r"(v.z), "r"(v.w) : "memory");
}
__device__ __forceinline__ void red_stat(void* p, float s, float q) {
    asm volatile("red.relaxed.gpu.global.add.v4.f32 [%0], {%1,%2,%3,%4};" ::"l"(p), "f"(s), "f"(q), "f"(1.0f), "f"(0.0f) : "memory");
}
__device__ __forceinline__ uint4 lds128(uint32_t a) {
    uint4 v;
    asm volatile("ld.shared.v4.u32 {%0,%1,%2,%3}, [%4];" : "=r"(v.x), "=r"(v.y), "=r"(v.z), "=r"(v.w) : "r"(a) : "memory");
    return v;
}
__device__ __forceinline__ uint4 lds128v(uint32_t a) {
    uint4 v;
    asm volatile("ld.volatile.shared.v4.u32 {%0,%1,%2,%3}, [%4];" : "=r"(v.x), "=r"(v.y), "=r"(v.z), "=r"(v.w) : "r"(a) : "memory");
    return v;
}
template <int BLK>
__device__ __forceinline__ void load_raw(uint32_t* seg, uint32_t base, uint32_t lo) {
#pragma unroll
    for (int i = 0; i < 9; i++) {
        const uint32_t z = ((lo >> 7) & 0x30) + (i + 4 * BLK) * 16;
        const uint32_t a = base + lo + ((z ^ (lo >> 3)) & 0x70) + ((z & 0x80) << 4) + BLK * 8192;
#pragma unroll
        for (int hh = 0; hh < 2; hh++) {
            const uint4 v = lds128(a + hh * 1024);
            uint32_t* d = seg + 36 * hh + 4 * i;
            d[0] = v.x; d[1] = v.y; d[2] = v.z; d[3] = v.w;
        }
    }
}
__device__ __forceinline__ void permute_raw(const uint32_t* seg, uint32_t* w) {
#pragma unroll
    for (int hh = 0; hh < 2; hh++)
#pragma unroll
        for (int el = 0; el < 36; el++)
            w[((el / 18) * 9 + el % 9) * 4 + ((el / 9) & 1) * 2 + hh] =
                __byte_perm(seg[36 * hh + (el >> 1)], seg[36 * hh + (el >> 1) + 18], (el & 1) ? 0x7632 : 0x5410);
}
__device__ __forceinline__ float2 lds64f(uint32_t a) {
    float2 v;
    asm volatile("ld.shared.v2.f32 {%0,%1}, [%2];" : "=f"(v.x), "=f"(v.y) : "r"(a) : "memory");
    return v;
}
__device__ __forceinline__ float lds32f(uint32_t a) {
    float v;
    asm volatile("ld.shared.f32 %0, [%1];" : "=f"(v) : "r"(a) : "memory");
    return v;
}
__device__ __forceinline__ void sts64f(uint32_t a, float x, float y) {
    asm volatile("st.shared.v2.f32 [%0], {%1,%2};" ::"r"(a), "f"(x), "f"(y) : "memory");
}
__device__ __forceinline__ void stsm4t(uint32_t a, uint32_t r0, uint32_t r1, uint32_t r2, uint32_t r3) {
    asm volatile("stmatrix.sync.aligned.m8n8.x4.trans.shared.b16 [%0], {%1,%2,%3,%4};" ::"r"(a), "r"(r0), "r"(r1), "r"(r2), "r"(r3) : "memory");
}
__device__ __forceinline__ float bf_lo(uint32_t r) { return __uint_as_float(r << 16); }
__device__ __forceinline__ float bf_hi(uint32_t r) { return __uint_as_float(r & 0xffff0000u); }
__device__ __forceinline__ uint32_t pack_bf(float lo, float hi) {
    uint32_t r;
    asm("cvt.rn.bf16x2.f32 %0, %1, %2;" : "=r"(r) : "f"(hi), "f"(lo));
    return r;
}
__device__ __forceinline__ uint32_t ldg_rlx32(const void* p) {
    uint32_t v;
    asm volatile("ld.relaxed.gpu.global.u32 %0, [%1];" : "=r"(v) : "l"(p) : "memory");
    return v;
}
__device__ __forceinline__ void stg_rlx32(void* p, uint32_t v) {
    asm volatile("st.relaxed.gpu.global.u32 [%0], %1;" ::"l"(p), "r"(v) : "memory");
}
__device__ __forceinline__ void reduce_publish(uint32_t a, int lane, void* dst, bool one) {
    const uint4 v0 = lds128(a), v1 = lds128(a + 256);
    float s = (__uint_as_float(v0.x) + __uint_as_float(v0.z)) + (__uint_as_float(v1.x) + __uint_as_float(v1.z));
    float q = (__uint_as_float(v0.y) + __uint_as_float(v0.w)) + (__uint_as_float(v1.y) + __uint_as_float(v1.w));
#pragma unroll
    for (int o = 1; o < 16; o <<= 1) {
        s += __shfl_xor_sync(~0u, s, o);
        q += __shfl_xor_sync(~0u, q, o);
    }
    if (one) { s += __shfl_xor_sync(~0u, s, 16); q += __shfl_xor_sync(~0u, q, 16); }
    if ((lane & (one ? 31 : 15)) == 0) red_stat(dst, s, q);
    __syncwarp();
}
__device__ __forceinline__ bool mbar_test(uint32_t bar, uint32_t par) {
    uint32_t ok;
    asm volatile("{.reg .pred p; mbarrier.test_wait.parity.shared::cta.b64 p, [%1], %2; selp.u32 %0, 1, 0, p;}"
                 : "=r"(ok) : "r"(bar), "r"(par) : "memory");
    return ok;
}
__device__ __forceinline__ void mbar_wait_t(bool ok, uint32_t bar, uint32_t par) {
    asm volatile(
        "{\n"
        ".reg .pred p;\n"
        ".reg .u32 n;\n"
        "setp.ne.u32 p, %2, 0;\n"
        "@p bra.uni WAIT_DONE;\n"
        "mov.u32 n, 0;\n"
        "WAIT_LOOP:\n"
        "mbarrier.try_wait.parity.shared::cta.b64 p, [%0], %1;\n"
        "@p bra.uni WAIT_DONE;\n"
        "add.u32 n, n, 1;\n"
        "setp.lt.u32 p, n, 100000;\n"
        "@p bra.uni WAIT_LOOP;\n"
        "trap;\n"
        "WAIT_DONE:\n"
        "}\n" ::"r"(bar), "r"(par), "r"((uint32_t)ok) : "memory");
}
__device__ __forceinline__ void arrive_elect(uint32_t bar) {
    asm volatile("{.reg .pred e; elect.sync _|e, 0xffffffff; @e mbarrier.arrive.shared::cta.b64 _, [%0];}" ::"r"(bar) : "memory");
}

struct Params {
    const __nv_bfloat16 *x, *t_emb;
    const __nv_bfloat16* gb[4];
    __nv_bfloat16* out;
    char* h;
    char* box;
};
__device__ __forceinline__ int acc_off(int half, int b, int grp) { return half * 512 + b * 256 + grp * 128; }
__device__ __forceinline__ int parity_of(uint32_t c0, uint32_t c1, float full) {
    return __uint_as_float(c0) == full && __uint_as_float(c1) != full;
}
__device__ __forceinline__ void bar_n(int id, int n) { asm volatile("bar.sync %0, %1;" ::"r"(id), "r"(n) : "memory"); }

#define TA(i) do { } while (0)
__device__ __noinline__ void aux_part(const Params p, const CUtensorMap* tme, char* sm, int tid) {
    const int e = blockIdx.x, c4 = tid & 3, er = tid >> 2;
    const uint32_t sb = smem_u32(sm);
    if (tid == 0) {
        const uint32_t bar = sb + SM_MISC + 8 * B_X1;
        mbar_init(bar, 1);
        mbar_expect_tx(bar, 49152);
#pragma unroll
        for (int i = 0; i < 3; i++)
            asm volatile("cp.async.bulk.tensor.2d.shared::cluster.global.mbarrier::complete_tx::bytes [%0], [%1, {%3, %4}], [%2];"
                         ::"r"(sb + SM_SA + i * 16384), "l"(tme), "r"(bar), "r"(32 * e), "r"(256 * i) : "memory");
    }
    TA(0);
    char* a1 = p.box + acc_off(e & 1, 1, e >> 1);
    const uint32_t c0 = ldg_rlx32(a1 + 8), c1 = ldg_rlx32(a1 + 40);
    uint32_t tv[3];
#pragma unroll
    for (int i = 0; i < 3; i++) tv[i] = __ldg((const uint32_t*)p.t_emb + tid + 256 * i);
    const int par = parity_of(c0, c1, 33.0f);
    float* st_s = (float*)(sm + SM_SA + 49152);
    float* red = st_s + 1536;
#pragma unroll
    for (int i = 0; i < 3; i++) {
        const float lo = bf_lo(tv[i]), hi = bf_hi(tv[i]);
        ((float2*)st_s)[tid + 256 * i] = make_float2(__fdividef(lo, 1.f + __expf(-lo)), __fdividef(hi, 1.f + __expf(-hi)));
    }
    bar_n(2, 256);
    TA(1);
    if (tid == 0) red_stat(a1 + 32 * par, 0.f, 0.f);
    mbar_wait(sb + SM_MISC + 8 * B_X1, 0);
    TA(2);
    float acc[16];
#pragma unroll
    for (int j = 0; j < 16; j++) acc[j] = 0.f;
#pragma unroll 4
    for (int i = 0; i < 12; i++) {
        const float s0 = st_s[er + 64 * i], s1 = st_s[768 + er + 64 * i];
        const uint4 wv = lds128(sb + SM_SA + tid * 16 + i * 4096);
        const uint32_t r[4] = {wv.x, wv.y, wv.z, wv.w};
#pragma unroll
        for (int j = 0; j < 4; j++) {
            const float lo = bf_lo(r[j]), hi = bf_hi(r[j]);
            acc[2 * j] = fmaf(s0, lo, acc[2 * j]);
            acc[2 * j + 1] = fmaf(s0, hi, acc[2 * j + 1]);
            acc[8 + 2 * j] = fmaf(s1, lo, acc[8 + 2 * j]);
            acc[8 + 2 * j + 1] = fmaf(s1, hi, acc[8 + 2 * j + 1]);
        }
    }
#pragma unroll
    for (int j = 0; j < 16; j++) {
        acc[j] += __shfl_xor_sync(~0u, acc[j], 4);
        acc[j] += __shfl_xor_sync(~0u, acc[j], 8);
        acc[j] += __shfl_xor_sync(~0u, acc[j], 16);
    }
    TA(3);
    if ((tid & 31) < 4) {
#pragma unroll
        for (int j = 0; j < 16; j++) red[(tid >> 5) * 64 + (j >> 3) * 32 + c4 * 8 + (j & 7)] = acc[j];
    }
    bar_n(2, 256);
    if (tid < 64) {
        float s0 = 0.f;
#pragma unroll
        for (int i = 0; i < 8; i++) s0 += red[i * 64 + tid];
        char* eb = p.box + BX_EMB + (tid >> 5) * 512 + (e * 32 + (tid & 31)) * 4;
        stg_rlx32(eb + par * 1024, __float_as_uint(s0) | 1u);
        stg_rlx32(eb + (par ^ 1) * 1024, 0u);
    }
    TA(4);
}

__device__ __forceinline__ void tma3(uint32_t dst, const CUtensorMap* tm, uint32_t bar, int c1, int c2) {
    asm volatile(
        "cp.async.bulk.tensor.3d.shared::cluster.global.mbarrier::complete_tx::bytes [%0], [%1, {%3, %4, %5}], [%2];"
        ::"r"(dst), "l"(tm), "r"(bar), "r"(0), "r"(c1), "r"(c2) : "memory");
}
__device__ __forceinline__ void prefetch_tm(const CUtensorMap* tm) { asm volatile("prefetch.tensormap [%0];" ::"l"(tm) : "memory"); }
__device__ __forceinline__ uint32_t fmabf2(uint32_t a, uint32_t b, uint32_t c) {
    uint32_t r;
    asm("fma.rn.bf16x2 %0, %1, %2, %3;" : "=r"(r) : "r"(a), "r"(b), "r"(c));
    return r;
}
__device__ __forceinline__ void mma16816(float (&c)[4], const uint4& a, uint32_t b0, uint32_t b1) {
    asm("mma.sync.aligned.m16n8k16.row.col.f32.bf16.bf16.f32 {%0,%1,%2,%3}, {%4,%5,%6,%7}, {%8,%9}, {%0,%1,%2,%3};"
        : "+f"(c[0]), "+f"(c[1]), "+f"(c[2]), "+f"(c[3]) : "r"(a.x), "r"(a.y), "r"(a.z), "r"(a.w), "r"(b0), "r"(b1));
}
__device__ __forceinline__ void mma1688(float (&c)[4], uint32_t a0, uint32_t a1, uint32_t b) {
    asm("mma.sync.aligned.m16n8k8.row.col.f32.bf16.bf16.f32 {%0,%1,%2,%3}, {%4,%5}, {%6}, {%0,%1,%2,%3};"
        : "+f"(c[0]), "+f"(c[1]), "+f"(c[2]), "+f"(c[3]) : "r"(a0), "r"(a1), "r"(b));
}
__device__ __forceinline__ void stat16(const uint4& r0, const uint4& r1, uint32_t dst, int lane) {
    float cs[4] = {0.f, 0.f, 0.f, 0.f}, ca[4] = {0.f, 0.f, 0.f, 0.f}, cb[4] = {0.f, 0.f, 0.f, 0.f};
    mma16816(cs, r0, 0x3f003f00u, 0x3f003f00u);
    mma16816(cs, r1, 0x3f003f00u, 0x3f003f00u);
    mma1688(ca, r0.x, r0.y, r0.x); mma1688(cb, r0.x, r0.y, r0.y);
    mma1688(ca, r0.z, r0.w, r0.z); mma1688(cb, r0.z, r0.w, r0.w);
    mma1688(ca, r1.x, r1.y, r1.x); mma1688(cb, r1.x, r1.y, r1.y);
    mma1688(ca, r1.z, r1.w, r1.z); mma1688(cb, r1.z, r1.w, r1.w);
    const float qd = (lane & 4) ? ca[1] + cb[3] : ca[0] + cb[2];
    if (((lane ^ (lane >> 3)) & 1) == 0) sts64f(dst, cs[0] + cs[2], (lane & 3) == (lane >> 3) ? qd : 0.f);
}
__device__ __forceinline__ uint32_t addbf2(uint32_t a, uint32_t b) {
    uint32_t r;
    asm("add.rn.bf16x2 %0, %1, %2;" : "=r"(r) : "r"(a), "r"(b));
    return r;
}
__device__ __forceinline__ uint4 pack_unit(const float (&v)[32], int u) {
    return make_uint4(pack_bf(v[u], v[4 + u]), pack_bf(v[8 + u], v[12 + u]), pack_bf(v[16 + u], v[20 + u]), pack_bf(v[24 + u], v[28 + u]));
}
__device__ __forceinline__ uint4 add_unit(const uint4& a, const uint4& b) {
    return make_uint4(addbf2(a.x, b.x), addbf2(a.y, b.y), addbf2(a.z, b.z), addbf2(a.w, b.w));
}
__device__ __forceinline__ void epi_store(const float (&accF)[32], uint4 (&P)[4], char* dst, uint32_t lo) {
#pragma unroll
    for (int u = 0; u < 4; u++) {
        P[u] = add_unit(pack_unit(accF, u), P[u]);
        P[u].x = max(P[u].x, lo);
        stg_rlx(dst + (u >> 1) * 65536 + (u & 1) * 64, P[u]);
    }
}
__device__ __forceinline__ void epi_stats(const uint4 (&P)[4], uint32_t red_sm) {
    float s[4] = {0.f, 0.f, 0.f, 0.f}, q[4] = {0.f, 0.f, 0.f, 0.f};
#pragma unroll
    for (int u = 0; u < 4; u++) {
        const uint32_t r[4] = {P[u].x, P[u].y, P[u].z, P[u].w};
#pragma unroll
        for (int i = 0; i < 4; i++) {
            const float lo = bf_lo(r[i]), hi = bf_hi(r[i]);
            s[u & 2] += lo; q[u & 2] = fmaf(lo, lo, q[u & 2]);
            s[(u & 2) + 1] += hi; q[(u & 2) + 1] = fmaf(hi, hi, q[(u & 2) + 1]);
        }
    }
    sts64f(red_sm, (s[0] + s[1]) + (s[2] + s[3]), (q[0] + q[1]) + (q[2] + q[3]));
}
template <int OFF>
__device__ __forceinline__ void load4_if(uint4 (&P)[4], uint32_t a0, uint32_t a1, bool on) {
    asm volatile(
        "{\n"
        ".reg .pred p;\n"
        "setp.ne.u32 p, %18, 0;\n"
        "@p ld.shared.v4.u32 {%0,%1,%2,%3}, [%16];\n"
        "@p ld.shared.v4.u32 {%4,%5,%6,%7}, [%17];\n"
        "@p ld.shared.v4.u32 {%8,%9,%10,%11}, [%16+%19];\n"
        "@p ld.shared.v4.u32 {%12,%13,%14,%15}, [%17+%19];\n"
        "}\n"
        : "+r"(P[0].x), "+r"(P[0].y), "+r"(P[0].z), "+r"(P[0].w), "+r"(P[1].x), "+r"(P[1].y), "+r"(P[1].z), "+r"(P[1].w),
          "+r"(P[2].x), "+r"(P[2].y), "+r"(P[2].z), "+r"(P[2].w), "+r"(P[3].x), "+r"(P[3].y), "+r"(P[3].z), "+r"(P[3].w)
        : "r"(a0), "r"(a1), "r"((uint32_t)on), "n"(OFF) : "memory");
}
__device__ __forceinline__ void send16(uint32_t dst, uint32_t bar, uint32_t a, uint32_t b, uint32_t c, uint32_t d) {
    asm volatile("st.async.weak.shared::cluster.mbarrier::complete_tx::bytes.v4.b32 [%0], {%1,%2,%3,%4}, [%5];"
                 ::"r"(dst), "r"(a), "r"(b), "r"(c), "r"(d), "r"(bar) : "memory");
}

struct Maps { CUtensorMap m[5]; };

__device__ __forceinline__ int img_row(int t, uint32_t o) { return min(max(2 * t - 1 + (int)(o & 3), 0), 63); }

__global__ void __cluster_dims__(2, 1, 1) __launch_bounds__(512, 1)
resblock_kernel(const __grid_constant__ Params p, const __grid_constant__ Maps tm) {
    extern __shared__ __align__(1024) char sm[];
    const uint32_t sb = smem_u32(sm), mb = sb + SM_MISC;
    const int idx = blockIdx.x - 4, k = idx & 1, m = (idx >> 1) & 1, t = idx >> 2, f = k ^ m;
    const int cen = 2 - f;
    const uint32_t seq = f ? 0xc9u : 0x1eu;
    const int tid = threadIdx.x, lane = tid & 31;
    uint4 r0, r1;
    if ((unsigned)(tid - 128) < 256u && idx >= 0) {
        r0 = ldg_nc((const char*)p.x + idx * 8192 + (tid - 128) * 16);
        r1 = ldg_nc((const char*)p.x + idx * 8192 + (tid - 128) * 16 + 4096);
    }
    const int wid = __shfl_sync(~0u, tid >> 5, 0);
    if (blockIdx.x < 4) {
        if (threadIdx.x < 256) aux_part(p, &tm.m[4], sm, threadIdx.x);
        return;
    }

    if (wid >= 12) {
        asm volatile("setmaxnreg.dec.sync.aligned.u32 64;");
        if (wid == 14) {
            TS(19);
            if (elect_one()) {
#pragma unroll
                for (int j = 0; j < 4; j++) mbar_init(mb + 8 * (B_W + j), 1);
#pragma unroll
                for (int j = 0; j < 4; j++) {
                    mbar_expect_tx(mb + 8 * (B_W + j), WPIECE);
                    tma3(sb + SM_WS + j * WPIECE, &tm.m[2], mb + 8 * (B_W + j), 64 * m + 16 * j, 9 * k);
                }
            }
            __syncwarp();
            TS2(20);
            asm volatile("bar.arrive 1, 160;" ::: "memory");
            asm volatile("barrier.cluster.arrive.relaxed.aligned;" ::: "memory");
            bar_n(5, 96);
#pragma unroll 1
            for (int j = 0; j < 8; j++) {
                constexpr uint64_t wa = (uint64_t)(B_W + XW0) | (uint64_t)(B_W + 3) << 8 | (uint64_t)B_STAT << 16 | (uint64_t)B_ROWA << 24 |
                                        (uint64_t)(B_ROWA + 7) << 32 | (uint64_t)(P1STAT ? B_STAT + 2 : B_X1) << 40 | (uint64_t)(B_WFREE + 1) << 48 |
                                        (uint64_t)(P1STAT ? B_STAT + 3 : B_X1) << 56;
                if (j >= 4) mbar_wait(mb + 8 * (B_FREE - 2 + (j >> 1)), 0);
                const uint32_t c0 = clock32();
                if (j >= XMODE) mbar_wait(mb + 8 * (uint32_t)((wa >> (8 * j)) & 63), 0);
                while (clock32() - c0 < (j < 4 ? 0 : ((j & 1) ? HDELAY2 : HDELAY))) { }
                const uint32_t dst = sb + (j < 4 ? SM_SA + j * 16384 : (j < 6 ? SM_SB : SM_WS) + (j & 1) * 16384);
                const int plane = (j & 2) * 64 + 64 * k + (j < 4 ? 0 : __float_as_uint(lds32f(sb + SM_PAR)) * 256);
                const uint32_t bar = mb + 8 * (B_S + j), rs = seq >> (4 * (j & 1));
                if (elect_one()) {
                    mbar_expect_tx(bar, 16384);
                    tma3(dst, &tm.m[j >> 2], bar, plane, img_row(t, rs));
                    tma3(dst + 8192, &tm.m[j >> 2], bar, plane, img_row(t, rs >> 2));
                }
                __syncwarp();
                TS2(j);
            }
            TS_DUMP();
            return;
        }
        if (wid == 12) {
            uint32_t tp = clock32() + PT0;
            const uint32_t oline = acc_off(idx >> 6, 0, (idx >> 5) & 1);
            const uint32_t c0 = ldg_rlx32(p.box + oline + 8), c1 = ldg_rlx32(p.box + oline + 40);
            uint32_t gb[4];
#pragma unroll
            for (int j = 0; j < 4; j++) asm volatile("ld.global.nc.u32 %0, [%1];" : "=r"(gb[j]) : "l"(p.gb[j] + 64 * k + 2 * lane));
            const int par = parity_of(c0, c1, 32.0f);
            asm volatile("st.shared.u32 [%0], %1;" ::"r"(sb + SM_PAR), "r"(par) : "memory");
            asm volatile("st.shared.v4.u32 [%0], {%1,%1,%1,%1};" ::"r"(sb + SM_COEF + 2048 + lane * 16), "r"(0) : "memory");
            asm volatile("barrier.cluster.arrive.relaxed.aligned;" ::: "memory");
            const uint32_t gl = (lane & 16) * 8 + par * 32;
#pragma unroll 1
            for (int gi = 0; gi < 4; gi++) {
                const int isH = gi >> 1;
                char* const bx = p.box + (gi & 1) * 256 + isH * 16;
                char* pub = bx + (isH ? m * 512 + gl : oline + par * 32);
                char* src = bx + k * 512 + gl;
                asm volatile("" : "+l"(pub), "+l"(src));
                if (isH) {
                    gb[0] = gb[2]; gb[1] = gb[3];
                    mbar_wait(mb + 8 * (B_FREE - 2 + gi), 0);
                } else {
                    bar_n(3 + gi, gi ? 288 : 352);
                }
                reduce_publish(sb + SM_RED + (gi & 1) * 1024 + (lane & 16) * 32 + (lane & 15) * 16, lane, pub, !isH);
                if (gi == 0) asm volatile("bar.arrive 6, 160;" ::: "memory");
                TS(4 + gi * 2);
                const uint32_t want = isH ? 0x42800000u : 0x42000000u + gi * 0x40000u;
                uint4 v = make_uint4(0, 0, want, 0);
                if (gi) tp = clock32() + PDELAY;
                while ((int)(clock32() - tp) < 0) { }
                int it = 0;
                do {
                    if ((lane & 15) == 0) v = ldg_rlx(src);
                } while (__any_sync(~0u, v.z != want) && ++it < SPIN_LIMIT);
                const float mean = __shfl_sync(~0u, __uint_as_float(v.x), lane & 16) * (1.0f / 131072.0f);
                const float msq = __shfl_sync(~0u, __uint_as_float(v.y), lane & 16) * (4.0f / 131072.0f);
                float rs;
                asm("rsqrt.approx.ftz.f32 %0, %1;" : "=f"(rs) : "f"(fmaxf(fmaf(-4.0f * mean, mean, msq), 0.f) + 4e-5f));
                const float a0 = rs * bf_lo(gb[0]), a1 = rs * bf_hi(gb[0]);
                const uint32_t ca0 = pack_bf(a0, a0), ca1 = pack_bf(a1, a1);
                const float b0 = fmaf(-mean, bf_hi(ca0), 0.5f * bf_lo(gb[1]));
                const float b1 = fmaf(-mean, bf_hi(ca1), 0.5f * bf_hi(gb[1]));
                asm volatile("st.shared.v4.u32 [%0], {%1,%2,%3,%4};" ::"r"(sb + SM_COEF + gi * 512 + lane * 16), "r"(ca0), "r"(pack_bf(b0, b0)),
                             "r"(ca1), "r"(pack_bf(b1, b1)) : "memory");
                __syncwarp();
                arrive_elect(mb + 8 * (B_STAT + gi));
                if ((idx | (lane & 15)) < 2 && (lane & 1) == 0) stg_rlx(bx + k * 512 + (gl ^ 32), make_uint4(0, 0, 0, 0));
                __syncwarp();
                TS(5 + gi * 2);
            }
        } else if (wid == 13) {
            if (elect_one()) {
                prefetch_tm(&tm.m[0]);
#pragma unroll
                for (int j = 0; j < B_W; j++) mbar_init(mb + 8 * j, j < B_FREE ? 8 : (j < B_P ? 4 : (j == B_SAFREE ? 2 : 1)));
#pragma unroll
                for (int j = 0; j < 4; j++) mbar_expect_tx(mb + 8 * (B_P + j), 8192);
                asm volatile("fence.mbarrier_init.release.cluster;" ::: "memory");
            }
            __syncwarp();
            TS2(20);
            asm volatile("bar.arrive 5, 96;" ::: "memory");
            asm volatile("bar.arrive 3, 352;" ::: "memory");
            asm volatile("barrier.cluster.arrive.relaxed.aligned;" ::: "memory");
            asm volatile("barrier.cluster.wait.aligned;" ::: "memory");
            uint32_t rbar;
            asm("mapa.shared::cluster.u32 %0, %1, %2;" : "=r"(rbar) : "r"(mb + 8 * B_SAFREE), "r"(k ^ 1));
#pragma unroll 1
            for (int j = 0; j < 16; j++) {
                const int o = (j & 7) * 8;
                if (j == 3 || j == 10) mbar_wait(mb + 8 * (j < 8 ? B_SAFREE : B_RES), 0);
                mbar_wait(mb + 8 * B_ROWA + o, j >> 3);
                asm volatile(
                    "{\n"
                    ".reg .pred e, r;\n"
                    "fence.proxy.async.shared::cta;\n"
                    "elect.sync _|e, 0xffffffff;\n"
                    "@e mbarrier.arrive.shared::cta.b64 _, [%0];\n"
                    "setp.eq.and.u32 r, %2, 1, e;\n"
                    "@r mbarrier.arrive.relaxed.cluster.shared::cluster.b64 _, [%1];\n"
                    "}\n" ::"r"(mb + 8 * B_ROW + o), "r"(rbar), "r"(j) : "memory");
                TS2(j);
            }
        } else {
            asm volatile("barrier.cluster.arrive.relaxed.aligned;" ::: "memory");
            bar_n(5, 96);
            for (const uint32_t c0 = clock32(); clock32() - c0 < XD;) { }
            if (elect_one()) {
                mbar_expect_tx(mb + 8 * B_X1, 8192);
                asm volatile("cp.async.bulk.shared::cluster.global.mbarrier::complete_tx::bytes [%0], [%1], %2, [%3];"
                             ::"r"(sb + SM_SB + 24576), "l"((const char*)p.x + (128 + idx) * 8192), "r"(8192), "r"(mb + 8 * B_X1) : "memory");
                prefetch_tm(&tm.m[1]);
            }
            bar_n(3, 352);
            const int par = __float_as_uint(lds32f(sb + SM_PAR));
            {
                mbar_wait(mb + 8 * (B_ROW + EROW), 0);
                uint4 e;
                int it = 0;
                do {
                    e = ldg_rlx(p.box + BX_EMB + par * 1024 + (lane >> 4) * 512 + m * 256 + (lane & 15) * 16);
                } while (__any_sync(~0u, min(min(e.x, e.y), min(e.z, e.w)) == 0u) && ++it < SPIN_LIMIT);
                const uint32_t r[4] = {e.x, e.y, e.z, e.w};
#pragma unroll
                for (int i = 0; i < 4; i++) {
                    const uint32_t v = pack_bf(__uint_as_float(r[i]), __uint_as_float(r[i]));
                    asm volatile("st.shared.v4.u32 [%0], {%1,%1,%1,%1};" ::"r"(sb + SM_EMB + lane * 64 + i * 16), "r"(v) : "memory");
                }
                __syncwarp();
                arrive_elect(mb + 8 * B_SAFREE);
                TS2(1);
            }
            mbar_wait(mb + 8 * B_WFREE, 0);
            mbar_wait(mb + 8 * (B_STAT + 1), 0);
            mbar_wait(mb + 8 * (B_ROW + 3), 0);
            if (elect_one()) {
#pragma unroll 1
                for (int j = 0; j < 4; j++) {
                    mbar_expect_tx(mb + 8 * (B_W + j), WPIECE);
                    tma3(sb + SM_WS + j * WPIECE, &tm.m[3], mb + 8 * (B_W + j), 64 * m + 16 * j, 9 * k);
                }
            }
            __syncwarp();
            if (elect_one()) {
                mbar_expect_tx(mb + 8 * B_RES, 16384);
                tma3(sb + SM_SA + 16384, &tm.m[0], mb + 8 * B_RES, 64 * m, 2 * t + 1 - f);
                tma3(sb + SM_SA + 24576, &tm.m[0], mb + 8 * B_RES, 128 + 64 * m, 2 * t + 1 - f);
            }
            mbar_wait(mb + 8 * (B_STAT + 3), 0);
            mbar_wait(mb + 8 * (B_ROW + 6), 1);
            uint4* oh = (uint4*)(p.h + (par ^ 1) * (2 << 20)) + idx * 1024 + lane;
#pragma unroll 1
            for (int u = 0; u < 32; u++) oh[u * 32] = make_uint4(0, 0, 0, 0);
        }
    } else if (wid >= 4) {
        const int ht = tid - 128, hw = wid - 4;
        asm volatile("barrier.cluster.arrive.relaxed.aligned;" ::: "memory");
        TS2(1);
        stat16(r0, r1, sb + SM_RED + (ht >> 1) * 8, lane);
        TS2(2);
        asm volatile("setmaxnreg.dec.sync.aligned.u32 96;");
        bar_n(3, 352);
        const int icl = (hw & 4) * 8 + (lane & 28) + (hw & 3);
        uint32_t st_lane = hw * CHUNK + (2 * (lane >> 3) + (lane & 1) + 1) * PLANE + ((lane >> 1) & 3) * 32;
        uint32_t dup_lane;
        {
            const int bd = ((lane >> 1) & 7) + ((lane & 1) ? 1 : -1);
            dup_lane = hw * CHUNK + ((lane & 1) ? 0 : 9 * PLANE) + (2 * (bd & 3) + ((bd >> 2) & 1)) * 16;
            if (bd < 0 || bd > 7) dup_lane = hw * CHUNK + PLANE + 16;
        }
        uint32_t ld0 = icl * 128 + (((lane & 3) ^ (icl & 7)) << 4), ld1 = ld0 ^ 64, cl = icl * 8;
        const int inv = t == 0 ? 3 - f : (t == 31 ? 1 + 2 * f : 4);
        asm volatile("" : "+r"(st_lane), "+r"(dup_lane), "+r"(ld0), "+r"(ld1), "+r"(cl));
        mbar_wait(mb + 8 * B_X1, 0);
        TS2(3);
        stat16(lds128(sb + SM_SB + 24576 + ht * 16), lds128(sb + SM_SB + 28672 + ht * 16), sb + SM_RED + 1024 + (ht >> 1) * 8, lane);
        asm volatile("bar.arrive 4, 288;" ::: "memory");
        TS2(20);
        uint4 X[4];
        float2 C[2];
        uint32_t stage = sb + SM_SA, coefA = sb + SM_COEF, coefB = sb + SM_COEF + (inv == 1 ? 2048 : 0);
        uint32_t cbar = mb + 8 * B_STAT;
        bool have = false, havec = false;
#pragma unroll 1
        for (int gp = 0; gp < 8; gp++) {
            const uint32_t rs = seq >> (4 * (gp & 1));
            if (!havec) {
              if (!have) {
                mbar_wait(mb + 8 * (B_S + gp), 0);
                TS2(21 + gp);
                X[0] = lds128(stage + ld0); X[1] = lds128(stage + ld1);
                X[2] = lds128(stage + 8192 + ld0); X[3] = lds128(stage + 8192 + ld1);
#pragma unroll 1
                for (int it = 0; gp >= 4 && __any_sync(~0u, min(min(X[0].x, X[1].x), min(X[2].x, X[3].x)) == 0u) && it < SPIN_LIMIT; it++) {
                    const char* src = p.h + (__float_as_uint(lds32f(sb + SM_PAR)) * 2 + ((gp >> 1) & 1)) * (1 << 20) + (64 * k + icl) * 8192 + (lane & 3) * 16;
                    const char* sa = src + img_row(t, rs) * 128;
                    const char* sc = src + img_row(t, rs >> 2) * 128;
                    X[0] = ldg_rlx(sa); X[1] = ldg_rlx(sa + 64);
                    X[2] = ldg_rlx(sc); X[3] = ldg_rlx(sc + 64);
                }
              }
                mbar_wait(cbar, 0);
                C[0] = lds64f(coefA + cl);
                C[1] = lds64f(coefB + cl);
            }
            const uint32_t opb = sb + SM_OP0 - (gp & 2) * (OPSZ / 2), abar = mb + 8 * B_ROWA + (gp & 3) * 16;
            uint32_t h[16];
#pragma unroll
            for (int u = 0; u < 4; u++) {
                const uint32_t ca = __float_as_uint(C[u >> 1].x), cb = __float_as_uint(C[u >> 1].y);
                h[4 * u] = fmabf2(X[u].x, ca, cb); h[4 * u + 1] = fmabf2(X[u].y, ca, cb);
                h[4 * u + 2] = fmabf2(X[u].z, ca, cb); h[4 * u + 3] = fmabf2(X[u].w, ca, cb);
            }
#pragma unroll
            for (int r = 0; r < 2; r++) {
                const uint32_t u0 = opb + ((rs >> (2 * r)) & 3) * 128;
                uint32_t* g = h + 8 * r;
#pragma unroll
                for (int i = 0; i < 8; i++) {
                    uint32_t th;
                    asm volatile("tanh.approx.bf16x2 %0, %1;" : "=r"(th) : "r"(g[i]));
                    g[i] = fmabf2(g[i], th, g[i]);
                }
                stsm4t(u0 + st_lane, g[0], g[1], g[2], g[3]);
                asm volatile("stmatrix.sync.aligned.m8n8.x2.trans.shared.b16 [%0], {%1,%2};"
                             ::"r"(u0 + dup_lane), "r"(__byte_perm(g[0], g[3], 0x7610)), "r"(__byte_perm(g[4], g[7], 0x7610)) : "memory");
                stsm4t(u0 + st_lane + 16, g[4], g[5], g[6], g[7]);
                arrive_elect(abar + 8 * r);
                if (PSYNC >> r & 1) bar_n(8 + (hw & 3), 64);
                TS(4 + 2 * gp + r);
                if (r == 0) {
                    stage += gp == 3 ? -16384 : (gp == 5 ? SM_WS - SM_SB - 16384 : 16384);
                    const uint32_t ct = sb + SM_COEF + ((gp + 1) >> 1) * 512, i0 = 2 * ((gp + 1) & 1);
                    coefA = i0 == inv ? sb + SM_COEF + 2048 : ct;
                    coefB = i0 + 1 == inv ? sb + SM_COEF + 2048 : ct;
                    cbar = mb + 8 * (HOLD && gp == 4 ? B_WFREE + 1 : B_STAT + ((gp + 1) >> 1));
                    const bool nx = mbar_test(mb + 8 * (B_S + gp + 1), 0), ns = mbar_test(cbar, 0);
                    X[0].x = 0;
                    asm volatile(
                        "{\n"
                        ".reg .pred p, c;\n"
                        "setp.ne.u32 p, %24, 0;\n"
                        "setp.ne.u32 c, %25, 0;\n"
                        "@p ld.shared.v4.u32 {%0,%1,%2,%3}, [%20];\n"
                        "@p ld.shared.v4.u32 {%4,%5,%6,%7}, [%21];\n"
                        "@p ld.shared.v4.u32 {%8,%9,%10,%11}, [%20+8192];\n"
                        "@p ld.shared.v4.u32 {%12,%13,%14,%15}, [%21+8192];\n"
                        "@c ld.shared.v2.f32 {%16,%17}, [%22];\n"
                        "@c ld.shared.v2.f32 {%18,%19}, [%23];\n"
                        "}\n"
                        : "+r"(X[0].x), "=r"(X[0].y), "=r"(X[0].z), "=r"(X[0].w), "=r"(X[1].x), "=r"(X[1].y), "=r"(X[1].z), "=r"(X[1].w),
                          "=r"(X[2].x), "=r"(X[2].y), "=r"(X[2].z), "=r"(X[2].w), "=r"(X[3].x), "=r"(X[3].y), "=r"(X[3].z), "=r"(X[3].w),
                          "=f"(C[0].x), "=f"(C[0].y), "=f"(C[1].x), "=f"(C[1].y)
                        : "r"(stage + ld0), "r"(stage + ld1), "r"(coefA + cl), "r"(coefB + cl), "r"((uint32_t)nx), "r"((uint32_t)ns) : "memory");
                    havec = ns;
                }
            }
            have = __all_sync(~0u, min(min(X[0].x, X[1].x), min(X[2].x, X[3].x)) != 0u);
            havec = __all_sync(~0u, havec) && have;
        }
    } else {
        const uint32_t t16 = tid * 16;
        {
            const uint32_t a = sb + SM_OP1 + (tid >> 3) * CHUNK + ((tid >> 1) & 3) * 128 + ((tid & 1) ? 9 * PLANE + 7 * 16 : 0);
            asm volatile("st.shared.v4.u32 [%0], {%1,%1,%1,%1};" ::"r"(a), "r"(0) : "memory");
            asm volatile("fence.proxy.async.shared::cta;" ::: "memory");
            asm volatile("barrier.cluster.arrive.relaxed.aligned;" ::: "memory");
        }
        bar_n(1, 160);
        bar_n(6, 160);
        asm volatile("setmaxnreg.inc.sync.aligned.u32 256;");
        const int par = __shfl_sync(~0u, __float_as_uint(lds32f(sb + SM_PAR)), 0);
        uint32_t W[144];
        float accS[32], accF[32];
        uint4 P[4];
        const uint32_t out_off = ((64 * m + 16 * wid + (lane >> 3) + (lane & 4)) * 64 + 2 * t + f) * 128 + (lane & 3) * 16;
        uint32_t rsb;
        asm("mapa.shared::cluster.u32 %0, %1, %2;" : "=r"(rsb) : "r"(sb), "r"(k ^ 1));
        const uint64_t dconst = ((uint64_t)(CHUNK / 16) << 16) | ((uint64_t)(PLANE / 16) << 32);
        const uint32_t d0 = (((sb + SM_OP0) & 0x3ffff) >> 4) + cen * 8;
        const uint32_t raddr = sb + SM_RED + tid * 8;
        const uint32_t eaddr = sb + SM_EMB + ((out_off >> 9) & 0x3f0);
        const uint32_t xaddr = sb + SM_SA + 16384 + ((out_off >> 6) & 0x1f80) + ((out_off ^ (out_off >> 9)) & 0x70);
        const uint32_t wbase = sb + SM_WS + wid * WPIECE;
#define WLO(v) uint32_t v = (lane & 3) * 2048 + ((lane >> 3) + (lane & 4)) * 128; asm volatile("" : "+r"(v))
        {
            WLO(lo);
            mbar_wait(mb + 8 * (B_W + wid), 0);
            load_raw<0>(W + 72, wbase, lo);
        }
#pragma unroll 1
        for (int cv = 0; cv < 2; cv++) {
        {
            TS2(3);
            WLO(lo);
            uint32_t seg[72];
            load_raw<1>(seg, wbase, lo);
            permute_raw(W + 72, W);
            permute_raw(seg, W + 72);
            arrive_elect(mb + 8 * (B_WFREE + cv));
            TS2(4);
        }
#pragma unroll
        for (int i = 0; i < 32; i++) accF[i] = 0.f;
#pragma unroll
        for (int i = 0; i < 4; i++) P[i] = make_uint4(0, 0, 0, 0);
#pragma unroll 1
        for (int b = 0;; b++) {
            const int it = 2 * cv + b;
            const uint32_t rb = mb + 8 * B_ROW + b * 32;
            const uint64_t dS = dconst | (uint64_t)(d0 - b * (OPSZ / 16));
            const uint64_t dF = dS + (uint64_t)(int64_t)(16 * f - 8);
            bool ok;
            if (b) {
                mbar_wait_t(false, mb + 8 * (B_P - 1 + it), 0);
#pragma unroll
                for (int u = 0; u < 4; u++) P[u] = lds128v(sb + SM_SA + (b - 1) * 8192 + u * 2048 + t16);
            }
            if (b < 2) {
                asm volatile(
                    "{\n"
                    ".reg .pred p;\n"
                    ".reg .u32 n;\n"
                    "mbarrier.test_wait.parity.shared::cta.b64 p, [%0], %2;\n"
                    "@p bra.uni ROW_DONE;\n"
                    "mov.u32 n, 0;\n"
                    "ROW_LOOP:\n"
                    "mbarrier.try_wait.parity.shared::cta.b64 p, [%1], %2;\n"
                    "@p bra.uni ROW_FENCE;\n"
                    "add.u32 n, n, 1;\n"
                    "setp.lt.u32 p, n, 100000;\n"
                    "@p bra.uni ROW_LOOP;\n"
                    "trap;\n"
                    "ROW_FENCE:\n"
                    "fence.proxy.async.shared::cta;\n"
                    "ROW_DONE:\n"
                    "}\n" ::"r"(rb), "r"(rb - 8 * (B_ROW - B_ROWA)), "r"(cv) : "memory");
                TS(8 + 4 * it);
                wg_fence();
                mma_sub<0>(accS, W, dS);
                mma_sub<1>(accS, W, dS);
                mma_sub<2>(accS, W, dS);
                ok = mbar_test(rb + 8, cv);
                mma_sub<3>(accS, W, dS);
                wg_commit();
                mbar_wait_t(ok, rb + 8, cv);
                TS3(1);
                wg_wait<1>();
            } else {
                wg_wait<0>();
                if (cv == 0) {
                    WLO(lo);
                    mbar_wait_t(false, mb + 8 * (B_W + wid), 1);
                    load_raw<0>(W + 72, wbase, lo);
                }
            }
            if (b) {
                TS3(2);
                acc_fence(accF);
                epi_store(accF, P, (cv ? (char*)p.out : p.h + par * (2 << 20)) + (b - 1) * (1 << 20) + out_off, cv ^ 1);
                TS3(5);
            }
            if (b < 2) {
                wg_fence();
                mma_sub<4>(accS, W, dS);
                mma_sub<5>(accS, W, dS);
            }
            if (b && cv == 0) {
                epi_stats(P, raddr + (b - 1) * 1024);
                __syncwarp();
                arrive_elect(mb + 8 * (B_FREE - 1 + b));
                TS2(9 + 4 * it);
            }
            if (b == 2) { wg_wait<0>(); break; }
            TS3(6);
            wg_fence();
            mma_sub<6>(accS, W, dS);
            ok = mbar_test(rb + 16, cv);
            mma_sub<7>(accS, W, dS);
            TS3(27);
            mbar_wait_t(ok, rb + 16, cv);
            TS3(7);
            load4_if<1024>(P, xaddr + b * 8192, (xaddr + b * 8192) ^ 64, cv);
            wg_fence();
            mma_sub<8>(accS, W, dS);
            mma_sub<9>(accS, W, dS);
            mma_sub<10>(accS, W, dS);
            mma_sub<11>(accS, W, dS);
            wg_commit();
            TS2(10 + 4 * it);
            wg_fence();
            mma_sub<0>(accF, W, dF);
            ok = mbar_test(rb + 24, cv);
            mma_sub<1>(accF, W, dF);
            wg_commit();
            TS3(28);
            mbar_wait_t(ok, rb + 24, cv);
            load4_if<128>(P, eaddr + b * 1024, eaddr + b * 1024, !cv);
            TS3(24);
            wg_fence();
            mma_sub<2>(accF, W, dF);
            wg_commit();
            wg_wait<2>();
            acc_fence(accS);
            TS3(25);
#define SEND(u) do { const uint4 o = add_unit(pack_unit(accS, u), P[u]); \
    send16(rsb + SM_SA + b * 8192 + (u) * 2048 + t16, rsb + SM_MISC + 8 * (B_P + it), o.x, o.y, o.z, o.w); } while (0)
            SEND(0); SEND(1); SEND(2); SEND(3);
            TS3(26);
            mma_sub<3>(accF, W, dF);
            mma_sub<4>(accF, W, dF);
            mma_sub<5>(accF, W, dF);
            mma_sub<6>(accF, W, dF);
            mma_sub<7>(accF, W, dF);
            mma_sub<8>(accF, W, dF);
            mma_sub<9>(accF, W, dF);
            mma_sub<10>(accF, W, dF);
            mma_sub<11>(accF, W, dF);
            wg_commit();
            TS2(11 + 4 * it);
        }
        }
    }
    TS(0);
    TS_DUMP();
}

typedef CUresult (*EncodeFn)(CUtensorMap*, CUtensorMapDataType, cuuint32_t, void*, const cuuint64_t*, const cuuint64_t*,
                             const cuuint32_t*, const cuuint32_t*, CUtensorMapInterleave, CUtensorMapSwizzle,
                             CUtensorMapL2promotion, CUtensorMapFloatOOBfill);

void make_wmap(EncodeFn enc, CUtensorMap* tm, void* w) {
    cuuint64_t gd[3] = {64, 128, 18};
    cuuint64_t gs[2] = {2304, 128};
    cuuint32_t bd[3] = {64, 16, 9};
    cuuint32_t es[3] = {1, 1, 1};
    enc(tm, CU_TENSOR_MAP_DATA_TYPE_BFLOAT16, 3, w, gd, gs, bd, es, CU_TENSOR_MAP_INTERLEAVE_NONE,
        CU_TENSOR_MAP_SWIZZLE_128B, CU_TENSOR_MAP_L2_PROMOTION_L2_128B, CU_TENSOR_MAP_FLOAT_OOB_FILL_NONE);
}

void make_amap(EncodeFn enc, CUtensorMap* tm, void* a, int planes, int rows) {
    cuuint64_t gd[3] = {64, (cuuint64_t)planes, 64};
    cuuint64_t gs[2] = {8192, 128};
    cuuint32_t bd[3] = {64, 64, (cuuint32_t)rows};
    cuuint32_t es[3] = {1, 1, 1};
    enc(tm, CU_TENSOR_MAP_DATA_TYPE_BFLOAT16, 3, a, gd, gs, bd, es, CU_TENSOR_MAP_INTERLEAVE_NONE,
        CU_TENSOR_MAP_SWIZZLE_128B, CU_TENSOR_MAP_L2_PROMOTION_L2_128B, CU_TENSOR_MAP_FLOAT_OOB_FILL_NONE);
}

}

extern "C" void kernel_launch(void* const* d_in, const int* in_sizes, int n_in, void* d_out, int out_size) {
    static EncodeFn enc = nullptr;
    static void *ph, *pbox;
    if (!enc) {
        cudaGetSymbolAddress(&ph, g_h);
        cudaGetSymbolAddress(&pbox, g_box);
        void* fn = nullptr;
        cudaDriverEntryPointQueryResult qr;
        cudaGetDriverEntryPoint("cuTensorMapEncodeTiled", &fn, cudaEnableDefault, &qr);
        enc = (EncodeFn)fn;
        cudaFuncSetAttribute(resblock_kernel, cudaFuncAttributeMaxDynamicSharedMemorySize, SMEM_BYTES);
    }
    Params p;
    p.x = (const __nv_bfloat16*)d_in[0];
    p.t_emb = (const __nv_bfloat16*)d_in[1];
    p.gb[0] = (const __nv_bfloat16*)d_in[2];
    p.gb[1] = (const __nv_bfloat16*)d_in[3];
    p.gb[2] = (const __nv_bfloat16*)d_in[6];
    p.gb[3] = (const __nv_bfloat16*)d_in[7];
    p.out = (__nv_bfloat16*)d_out;
    p.h = (char*)ph;
    p.box = (char*)pbox;
    Maps tm;
    {
        cuuint64_t gd[2] = {128, 768};
        cuuint64_t gs[1] = {256};
        cuuint32_t bd[2] = {32, 256};
        cuuint32_t es[2] = {1, 1};
        enc(&tm.m[4], CU_TENSOR_MAP_DATA_TYPE_BFLOAT16, 2, d_in[5], gd, gs, bd, es, CU_TENSOR_MAP_INTERLEAVE_NONE,
            CU_TENSOR_MAP_SWIZZLE_NONE, CU_TENSOR_MAP_L2_PROMOTION_NONE, CU_TENSOR_MAP_FLOAT_OOB_FILL_NONE);
    }
    make_amap(enc, &tm.m[0], d_in[0], 256, 1);
    make_amap(enc, &tm.m[1], ph, 512, 1);
    make_wmap(enc, &tm.m[2], d_in[4]);
    make_wmap(enc, &tm.m[3], d_in[8]);
    resblock_kernel<<<132, 512, SMEM_BYTES>>>(p, tm);
}
```

```cpp
#include <cuda_runtime.h>
#include <cuda_bf16.h>
#include <cuda.h>
#include <stdint.h>

namespace {

constexpr int PLANE = 528;
constexpr int CHUNK = 10 * PLANE;
constexpr int OPSZ = 8 * CHUNK;
constexpr int WPIECE = 18432;
constexpr int WSZ = 4 * WPIECE;
constexpr int SM_WS = 0;
constexpr int SM_SA = WSZ;
constexpr int SM_SB = SM_SA + 32768;
constexpr int SM_OP1 = SM_SB + 32768;
constexpr int SM_OP0 = SM_OP1 + OPSZ;
constexpr int SM_MISC = SM_OP0 + OPSZ;
constexpr int B_ROWA = 0;
constexpr int B_Q = 8;
constexpr int B_WFREE = 12;
constexpr int B_FREE = 14;
constexpr int B_P = 16;
constexpr int B_ROW = 20;
constexpr int B_PFREE = 28;
constexpr int B_X1 = 31;
constexpr int B_S = 32;
constexpr int B_STAT = 40;
constexpr int B_W = 44;
constexpr int SM_PAR = SM_MISC + 448;
constexpr int SM_COEF = SM_MISC + 512;
constexpr int SM_RED = SM_COEF + 2560;
constexpr int SM_TS = SM_RED + 2048 + 64;
constexpr int SMEM_BYTES = SM_TS;
#define TIT 1
#define HDELAY2 100
#define P1STAT 0
#define XMODE 0
#define PDELAY 350
#define HOLD 1
#define XD 500
#define PT0 2250
#define XW0 0
#define HDELAY 100
constexpr int SPIN_LIMIT = 200000;

__device__ uint4 g_h[2 * 2 * 128 * 64 * 8];
__device__ __align__(128) uint4 g_box[192];
constexpr int BX_EMB = 1024;
#define TS3(id) do { } while (0)
#define TS2(id) do { } while (0)
#define TS(id) do { } while (0)
#define TS_DUMP() do { } while (0)

__device__ __forceinline__ uint32_t smem_u32(const void* p) { return (uint32_t)__cvta_generic_to_shared(p); }
__device__ __forceinline__ void mbar_init(uint32_t bar, int cnt) {
    asm volatile("mbarrier.init.shared::cta.b64 [%0], %1;" ::"r"(bar), "r"(cnt) : "memory");
}
__device__ __forceinline__ void mbar_expect_tx(uint32_t bar, uint32_t bytes) {
    asm volatile("mbarrier.arrive.expect_tx.shared::cta.b64 _, [%0], %1;" ::"r"(bar), "r"(bytes) : "memory");
}
__device__ __forceinline__ void mbar_wait(uint32_t bar, uint32_t par) {
    asm volatile(
        "{\n"
        ".reg .pred p;\n"
        ".reg .u32 n;\n"
        "mov.u32 n, 0;\n"
        "WAIT_LOOP:\n"
        "mbarrier.try_wait.parity.shared::cta.b64 p, [%0], %1;\n"
        "add.u32 n, n, 1;\n"
        "setp.lt.and.u32 p, n, 100000, !p;\n"
        "@p bra.uni WAIT_LOOP;\n"
        "}\n" ::"r"(bar), "r"(par) : "memory");
}
__device__ __forceinline__ uint32_t clock32() {
    uint32_t c;
    asm volatile("mov.u32 %0, %%clock;" : "=r"(c));
    return c;
}
__device__ __forceinline__ bool elect_one() {
    uint32_t r;
    asm volatile("{.reg .pred p; elect.sync _|p, 0xffffffff; selp.u32 %0, 1, 0, p;}" : "=r"(r));
    return r;
}
__device__ __forceinline__ void wg_fence() { asm volatile("wgmma.fence.sync.aligned;" ::: "memory"); }
__device__ __forceinline__ void wg_commit() { asm volatile("wgmma.commit_group.sync.aligned;" ::: "memory"); }
template <int N> __device__ __forceinline__ void wg_wait() {
    asm volatile("wgmma.wait_group.sync.aligned %0;" ::"n"(N) : "memory");
}
__device__ __forceinline__ void wgmma_acc(float (&d)[32], const uint32_t* a, uint64_t desc) {
    asm volatile(
        "wgmma.mma_async.sync.aligned.m64n64k16.f32.bf16.bf16 "
        "{%0,%1,%2,%3,%4,%5,%6,%7,%8,%9,%10,%11,%12,%13,%14,%15,%16,%17,%18,%19,%20,%21,%22,%23,%24,%25,%26,%27,%28,%29,%30,%31}, "
        "{%32,%33,%34,%35}, %36, 1, 1, 1, 0;\n"
        : "+f"(d[0]), "+f"(d[1]), "+f"(d[2]), "+f"(d[3]), "+f"(d[4]), "+f"(d[5]), "+f"(d[6]), "+f"(d[7]), "+f"(d[8]), "+f"(d[9]), "+f"(d[10]), "+f"(d[11]), "+f"(d[12]), "+f"(d[13]), "+f"(d[14]), "+f"(d[15]), "+f"(d[16]), "+f"(d[17]), "+f"(d[18]), "+f"(d[19]), "+f"(d[20]), "+f"(d[21]), "+f"(d[22]), "+f"(d[23]), "+f"(d[24]), "+f"(d[25]), "+f"(d[26]), "+f"(d[27]), "+f"(d[28]), "+f"(d[29]), "+f"(d[30]), "+f"(d[31])
        : "r"(a[0]), "r"(a[1]), "r"(a[2]), "r"(a[3]), "l"(desc));
}
__device__ __forceinline__ void wgmma_first(float (&d)[32], const uint32_t* a, uint64_t desc) {
    asm volatile(
        "wgmma.mma_async.sync.aligned.m64n64k16.f32.bf16.bf16 "
        "{%0,%1,%2,%3,%4,%5,%6,%7,%8,%9,%10,%11,%12,%13,%14,%15,%16,%17,%18,%19,%20,%21,%22,%23,%24,%25,%26,%27,%28,%29,%30,%31}, "
        "{%32,%33,%34,%35}, %36, 0, 1, 1, 0;\n"
        : "=f"(d[0]), "=f"(d[1]), "=f"(d[2]), "=f"(d[3]), "=f"(d[4]), "=f"(d[5]), "=f"(d[6]), "=f"(d[7]), "=f"(d[8]), "=f"(d[9]), "=f"(d[10]), "=f"(d[11]), "=f"(d[12]), "=f"(d[13]), "=f"(d[14]), "=f"(d[15]), "=f"(d[16]), "=f"(d[17]), "=f"(d[18]), "=f"(d[19]), "=f"(d[20]), "=f"(d[21]), "=f"(d[22]), "=f"(d[23]), "=f"(d[24]), "=f"(d[25]), "=f"(d[26]), "=f"(d[27]), "=f"(d[28]), "=f"(d[29]), "=f"(d[30]), "=f"(d[31])
        : "r"(a[0]), "r"(a[1]), "r"(a[2]), "r"(a[3]), "l"(desc));
}
__device__ __forceinline__ void acc_fence(float (&d)[32]) {
#pragma unroll
    for (int i = 0; i < 32; i++) asm volatile("" : "+f"(d[i])::"memory");
}
template <int SUB>
__device__ __forceinline__ void mma_sub(float (&acc)[32], const uint32_t (&W)[144], uint64_t dcen) {
    constexpr int RG = SUB / 4, KS = SUB % 4;
    constexpr int TI = RG == 0 ? 1 : (RG == 1 ? 2 : 0);
    constexpr int ROFF = (TI - 1) * 8;
#pragma unroll
    for (int dx = 0; dx < 3; dx++) {
        uint64_t d = dcen + (uint64_t)(int64_t)(KS * (2 * CHUNK / 16) + dx * (PLANE / 16) + ROFF);
        if (SUB == 0 && dx == 0) wgmma_first(acc, &W[(KS * 9 + TI * 3 + dx) * 4], d);
        else wgmma_acc(acc, &W[(KS * 9 + TI * 3 + dx) * 4], d);
    }
}
__device__ __forceinline__ uint4 ldg_nc(const void* p) {
    uint4 v;
    asm volatile("ld.global.nc.L1::no_allocate.v4.u32 {%0,%1,%2,%3}, [%4];"
                 : "=r"(v.x), "=r"(v.y), "=r"(v.z), "=r"(v.w) : "l"(p));
    return v;
}
__device__ __forceinline__ uint4 ldg_rlx(const void* p) {
    uint4 v;
    asm volatile("ld.relaxed.gpu.global.v4.u32 {%0,%1,%2,%3}, [%4];"
                 : "=r"(v.x), "=r"(v.y), "=r"(v.z), "=r"(v.w) : "l"(p) : "memory");
    return v;
}
__device__ __forceinline__ void stg_rlx(void* p, uint4 v) {
    asm volatile("st.relaxed.gpu.global.v4.u32 [%0], {%1,%2,%3,%4};" ::"l"(p), "r"(v.x), "r"(v.y), "r"(v.z), "r"(v.w) : "memory");
}
__device__ __forceinline__ void red_stat(void* p, float s, float q) {
    asm volatile("red.relaxed.gpu.global.add.v4.f32 [%0], {%1,%2,%3,%4};" ::"l"(p), "f"(s), "f"(q), "f"(1.0f), "f"(0.0f) : "memory");
}
__device__ __forceinline__ uint4 lds128(uint32_t a) {
    uint4 v;
    asm volatile("ld.shared.v4.u32 {%0,%1,%2,%3}, [%4];" : "=r"(v.x), "=r"(v.y), "=r"(v.z), "=r"(v.w) : "r"(a) : "memory");
    return v;
}
template <int BLK>
__device__ __forceinline__ void load_raw(uint32_t* seg, uint32_t base, uint32_t lo) {
#pragma unroll
    for (int i = 0; i < 9; i++) {
        const uint32_t z = ((lo >> 7) & 0x30) + (i + 4 * BLK) * 16;
        const uint32_t a = base + lo + ((z ^ (lo >> 3)) & 0x70) + ((z & 0x80) << 4) + BLK * 8192;
#pragma unroll
        for (int hh = 0; hh < 2; hh++) {
            const uint4 v = lds128(a + hh * 1024);
            uint32_t* d = seg + 36 * hh + 4 * i;
            d[0] = v.x; d[1] = v.y; d[2] = v.z; d[3] = v.w;
        }
    }
}
__device__ __forceinline__ void permute_raw(const uint32_t* seg, uint32_t* w) {
#pragma unroll
    for (int hh = 0; hh < 2; hh++)
#pragma unroll
        for (int el = 0; el < 36; el++)
            w[((el / 18) * 9 + el % 9) * 4 + ((el / 9) & 1) * 2 + hh] =
                __byte_perm(seg[36 * hh + (el >> 1)], seg[36 * hh + (el >> 1) + 18], (el & 1) ? 0x7632 : 0x5410);
}
__device__ __forceinline__ float2 lds64f(uint32_t a) {
    float2 v;
    asm volatile("ld.shared.v2.f32 {%0,%1}, [%2];" : "=f"(v.x), "=f"(v.y) : "r"(a) : "memory");
    return v;
}
__device__ __forceinline__ float lds32f(uint32_t a) {
    float v;
    asm volatile("ld.shared.f32 %0, [%1];" : "=f"(v) : "r"(a) : "memory");
    return v;
}
__device__ __forceinline__ void sts64f(uint32_t a, float x, float y) {
    asm volatile("st.shared.v2.f32 [%0], {%1,%2};" ::"r"(a), "f"(x), "f"(y) : "memory");
}
__device__ __forceinline__ void stsm4t(uint32_t a, uint32_t r0, uint32_t r1, uint32_t r2, uint32_t r3) {
    asm volatile("stmatrix.sync.aligned.m8n8.x4.trans.shared.b16 [%0], {%1,%2,%3,%4};" ::"r"(a), "r"(r0), "r"(r1), "r"(r2), "r"(r3) : "memory");
}
__device__ __forceinline__ float bf_lo(uint32_t r) { return __uint_as_float(r << 16); }
__device__ __forceinline__ float bf_hi(uint32_t r) { return __uint_as_float(r & 0xffff0000u); }
__device__ __forceinline__ uint32_t pack_bf(float lo, float hi) {
    uint32_t r;
    asm("cvt.rn.bf16x2.f32 %0, %1, %2;" : "=r"(r) : "f"(hi), "f"(lo));
    return r;
}
__device__ __forceinline__ uint32_t ldg_rlx32(const void* p) {
    uint32_t v;
    asm volatile("ld.relaxed.gpu.global.u32 %0, [%1];" : "=r"(v) : "l"(p) : "memory");
    return v;
}
__device__ __forceinline__ void stg_rlx32(void* p, uint32_t v) {
    asm volatile("st.relaxed.gpu.global.u32 [%0], %1;" ::"l"(p), "r"(v) : "memory");
}
__device__ __forceinline__ void warp_sum2(float& s, float& q) {
#pragma unroll
    for (int o = 1; o < 32; o <<= 1) {
        s += __shfl_xor_sync(~0u, s, o);
        q += __shfl_xor_sync(~0u, q, o);
    }
}
__device__ __forceinline__ bool mbar_test(uint32_t bar, uint32_t par) {
    uint32_t ok;
    asm volatile("{.reg .pred p; mbarrier.test_wait.parity.shared::cta.b64 p, [%1], %2; selp.u32 %0, 1, 0, p;}"
                 : "=r"(ok) : "r"(bar), "r"(par) : "memory");
    return ok;
}
__device__ __forceinline__ void mbar_wait_t(bool ok, uint32_t bar, uint32_t par) {
    asm volatile(
        "{\n"
        ".reg .pred p;\n"
        ".reg .u32 n;\n"
        "setp.ne.u32 p, %2, 0;\n"
        "@p bra.uni WAIT_DONE;\n"
        "mov.u32 n, 0;\n"
        "WAIT_LOOP:\n"
        "mbarrier.try_wait.parity.shared::cta.b64 p, [%0], %1;\n"
        "@p bra.uni WAIT_DONE;\n"
        "add.u32 n, n, 1;\n"
        "setp.lt.u32 p, n, 100000;\n"
        "@p bra.uni WAIT_LOOP;\n"
        "trap;\n"
        "WAIT_DONE:\n"
        "}\n" ::"r"(bar), "r"(par), "r"((uint32_t)ok) : "memory");
}
__device__ __forceinline__ void arrive_elect(uint32_t bar) {
    asm volatile("{.reg .pred e; elect.sync _|e, 0xffffffff; @e mbarrier.arrive.shared::cta.b64 _, [%0];}" ::"r"(bar) : "memory");
}

struct Params {
    const __nv_bfloat16 *x, *t_emb;
    const __nv_bfloat16* gb[4];
    __nv_bfloat16* out;
    char* h;
    char* box;
};
__device__ __forceinline__ int acc_off(int half, int b, int grp) { return half * 512 + b * 256 + grp * 128; }
__device__ __forceinline__ int parity_of(uint32_t c0, uint32_t c1, float full) {
    return __uint_as_float(c0) == full && __uint_as_float(c1) != full;
}
__device__ __forceinline__ void bar_n(int id, int n) { asm volatile("bar.sync %0, %1;" ::"r"(id), "r"(n) : "memory"); }

#define TA(i) do { } while (0)
__device__ __noinline__ void aux_part(const Params p, const CUtensorMap* tme, char* sm, int tid) {
    const int e = blockIdx.x, c4 = tid & 3, er = tid >> 2;
    const uint32_t sb = smem_u32(sm);
    if (tid == 0) {
        const uint32_t bar = sb + SM_MISC + 8 * B_X1;
        mbar_init(bar, 1);
        mbar_expect_tx(bar, 49152);
#pragma unroll
        for (int i = 0; i < 3; i++)
            asm volatile("cp.async.bulk.tensor.2d.shared::cluster.global.mbarrier::complete_tx::bytes [%0], [%1, {%3, %4}], [%2];"
                         ::"r"(sb + SM_SA + i * 16384), "l"(tme), "r"(bar), "r"(32 * e), "r"(256 * i) : "memory");
    }
    TA(0);
    char* a1 = p.box + acc_off(e & 1, 1, e >> 1);
    const uint32_t c0 = ldg_rlx32(a1 + 8), c1 = ldg_rlx32(a1 + 40);
    uint32_t tv[3];
#pragma unroll
    for (int i = 0; i < 3; i++) tv[i] = __ldg((const uint32_t*)p.t_emb + tid + 256 * i);
    const int par = parity_of(c0, c1, 33.0f);
    float* st_s = (float*)(sm + SM_SA + 49152);
    float* red = st_s + 1536;
#pragma unroll
    for (int i = 0; i < 3; i++) {
        const float lo = bf_lo(tv[i]), hi = bf_hi(tv[i]);
        ((float2*)st_s)[tid + 256 * i] = make_float2(__fdividef(lo, 1.f + __expf(-lo)), __fdividef(hi, 1.f + __expf(-hi)));
    }
    bar_n(2, 256);
    TA(1);
    if (tid == 0) red_stat(a1 + 32 * par, 0.f, 0.f);
    mbar_wait(sb + SM_MISC + 8 * B_X1, 0);
    TA(2);
    float acc[16];
#pragma unroll
    for (int j = 0; j < 16; j++) acc[j] = 0.f;
#pragma unroll 4
    for (int i = 0; i < 12; i++) {
        const float s0 = st_s[er + 64 * i], s1 = st_s[768 + er + 64 * i];
        const uint4 wv = lds128(sb + SM_SA + tid * 16 + i * 4096);
        const uint32_t r[4] = {wv.x, wv.y, wv.z, wv.w};
#pragma unroll
        for (int j = 0; j < 4; j++) {
            const float lo = bf_lo(r[j]), hi = bf_hi(r[j]);
            acc[2 * j] = fmaf(s0, lo, acc[2 * j]);
            acc[2 * j + 1] = fmaf(s0, hi, acc[2 * j + 1]);
            acc[8 + 2 * j] = fmaf(s1, lo, acc[8 + 2 * j]);
            acc[8 + 2 * j + 1] = fmaf(s1, hi, acc[8 + 2 * j + 1]);
        }
    }
#pragma unroll
    for (int j = 0; j < 16; j++) {
        acc[j] += __shfl_xor_sync(~0u, acc[j], 4);
        acc[j] += __shfl_xor_sync(~0u, acc[j], 8);
        acc[j] += __shfl_xor_sync(~0u, acc[j], 16);
    }
    TA(3);
    if ((tid & 31) < 4) {
#pragma unroll
        for (int j = 0; j < 16; j++) red[(tid >> 5) * 64 + (j >> 3) * 32 + c4 * 8 + (j & 7)] = acc[j];
    }
    bar_n(2, 256);
    if (tid < 64) {
        float s0 = 0.f;
#pragma unroll
        for (int i = 0; i < 8; i++) s0 += red[i * 64 + tid];
        char* eb = p.box + BX_EMB + (tid >> 5) * 512 + (e * 32 + (tid & 31)) * 4;
        stg_rlx32(eb + par * 1024, __float_as_uint(s0) | 1u);
        stg_rlx32(eb + (par ^ 1) * 1024, 0u);
    }
    TA(4);
}

__device__ __forceinline__ void tma3(uint32_t dst, const CUtensorMap* tm, uint32_t bar, int c1, int c2) {
    asm volatile(
        "cp.async.bulk.tensor.3d.shared::cluster.global.mbarrier::complete_tx::bytes [%0], [%1, {%3, %4, %5}], [%2];"
        ::"r"(dst), "l"(tm), "r"(bar), "r"(0), "r"(c1), "r"(c2) : "memory");
}
__device__ __forceinline__ void prefetch_tm(const CUtensorMap* tm) { asm volatile("prefetch.tensormap [%0];" ::"l"(tm) : "memory"); }
__device__ __forceinline__ uint32_t fmabf2(uint32_t a, uint32_t b, uint32_t c) {
    uint32_t r;
    asm("fma.rn.bf16x2 %0, %1, %2, %3;" : "=r"(r) : "r"(a), "r"(b), "r"(c));
    return r;
}
__device__ __forceinline__ void mma16816(float (&c)[4], const uint4& a, uint32_t b0, uint32_t b1) {
    asm("mma.sync.aligned.m16n8k16.row.col.f32.bf16.bf16.f32 {%0,%1,%2,%3}, {%4,%5,%6,%7}, {%8,%9}, {%0,%1,%2,%3};"
        : "+f"(c[0]), "+f"(c[1]), "+f"(c[2]), "+f"(c[3]) : "r"(a.x), "r"(a.y), "r"(a.z), "r"(a.w), "r"(b0), "r"(b1));
}
__device__ __forceinline__ void mma1688(float (&c)[4], uint32_t a0, uint32_t a1, uint32_t b) {
    asm("mma.sync.aligned.m16n8k8.row.col.f32.bf16.bf16.f32 {%0,%1,%2,%3}, {%4,%5}, {%6}, {%0,%1,%2,%3};"
        : "+f"(c[0]), "+f"(c[1]), "+f"(c[2]), "+f"(c[3]) : "r"(a0), "r"(a1), "r"(b));
}
__device__ __forceinline__ void stat16(const uint4& r0, const uint4& r1, uint32_t dst, int lane) {
    float cs[4] = {0.f, 0.f, 0.f, 0.f}, ca[4] = {0.f, 0.f, 0.f, 0.f}, cb[4] = {0.f, 0.f, 0.f, 0.f};
    mma16816(cs, r0, 0x3f003f00u, 0x3f003f00u);
    mma16816(cs, r1, 0x3f003f00u, 0x3f003f00u);
    mma1688(ca, r0.x, r0.y, r0.x); mma1688(cb, r0.x, r0.y, r0.y);
    mma1688(ca, r0.z, r0.w, r0.z); mma1688(cb, r0.z, r0.w, r0.w);
    mma1688(ca, r1.x, r1.y, r1.x); mma1688(cb, r1.x, r1.y, r1.y);
    mma1688(ca, r1.z, r1.w, r1.z); mma1688(cb, r1.z, r1.w, r1.w);
    const float qd = (lane & 4) ? ca[1] + cb[3] : ca[0] + cb[2];
    if (((lane ^ (lane >> 3)) & 1) == 0) sts64f(dst, cs[0] + cs[2], (lane & 3) == (lane >> 3) ? qd : 0.f);
}
__device__ __forceinline__ uint32_t addbf2(uint32_t a, uint32_t b) {
    uint32_t r;
    asm("add.rn.bf16x2 %0, %1, %2;" : "=r"(r) : "r"(a), "r"(b));
    return r;
}
__device__ __forceinline__ uint4 pack_unit(const float (&v)[32], int u) {
    return make_uint4(pack_bf(v[u], v[4 + u]), pack_bf(v[8 + u], v[12 + u]), pack_bf(v[16 + u], v[20 + u]), pack_bf(v[24 + u], v[28 + u]));
}
__device__ __forceinline__ uint4 add_unit(const uint4& a, const uint4& b) {
    return make_uint4(addbf2(a.x, b.x), addbf2(a.y, b.y), addbf2(a.z, b.z), addbf2(a.w, b.w));
}
__device__ __forceinline__ void send16(uint32_t dst, uint32_t bar, uint32_t a, uint32_t b, uint32_t c, uint32_t d) {
    asm volatile("st.async.weak.shared::cluster.mbarrier::complete_tx::bytes.v4.b32 [%0], {%1,%2,%3,%4}, [%5];"
                 ::"r"(dst), "r"(a), "r"(b), "r"(c), "r"(d), "r"(bar) : "memory");
}

struct Maps { CUtensorMap m[5]; };

__device__ __forceinline__ int img_row(int t, uint32_t o) { return min(max(2 * t - 1 + (int)(o & 3), 0), 63); }

__global__ void __cluster_dims__(2, 1, 1) __launch_bounds__(640, 1)
resblock_kernel(const __grid_constant__ Params p, const __grid_constant__ Maps tm) {
    extern __shared__ __align__(1024) char sm[];
    const uint32_t sb = smem_u32(sm), mb = sb + SM_MISC;
    const int idx = blockIdx.x - 4, k = idx & 1, m = (idx >> 1) & 1, t = idx >> 2, f = k ^ m;
    const int cen = 2 - f;
    const uint32_t seq = f ? 0xc9u : 0x1eu;
    const int tid = threadIdx.x, lane = tid & 31;
    uint4 r0, r1;
    if ((unsigned)(tid - 128) < 256u && idx >= 0) {
        r0 = ldg_nc((const char*)p.x + idx * 8192 + (tid - 128) * 16);
        r1 = ldg_nc((const char*)p.x + idx * 8192 + (tid - 128) * 16 + 4096);
    }
    const int wid = __shfl_sync(~0u, tid >> 5, 0);
    if (blockIdx.x < 4) {
        if (threadIdx.x < 256) aux_part(p, &tm.m[4], sm, threadIdx.x);
        return;
    }

    if (wid >= 16) {
        asm volatile("setmaxnreg.dec.sync.aligned.u32 64;");
        asm volatile("barrier.cluster.arrive.relaxed.aligned;" ::: "memory");
        const int w = wid - 16, och = 64 * m + 16 * w + (lane >> 3) + (lane & 4);
        const uint32_t out_off = (och * 64 + 2 * t + f) * 128 + (lane & 3) * 16, pa = sb + SM_SA + (tid & 127) * 16;
        uint32_t rbar;
        asm("mapa.shared::cluster.u32 %0, %1, %2;" : "=r"(rbar) : "r"(mb + 8 * (B_PFREE + 1)), "r"(k ^ 1));
        bar_n(3, 480);
        const int par = __shfl_sync(~0u, __float_as_uint(lds32f(sb + SM_PAR)), 0);
        if (w < 2) {
            if (w) bar_n(4, 288);
            const uint4 v0 = lds128(sb + SM_RED + w * 1024 + lane * 16), v1 = lds128(sb + SM_RED + w * 1024 + 512 + lane * 16);
            float s = (__uint_as_float(v0.x) + __uint_as_float(v0.z)) + (__uint_as_float(v1.x) + __uint_as_float(v1.z));
            float q = (__uint_as_float(v0.y) + __uint_as_float(v0.w)) + (__uint_as_float(v1.y) + __uint_as_float(v1.w));
            warp_sum2(s, q);
            if (lane == 0) red_stat(p.box + acc_off(idx >> 6, w, (idx >> 5) & 1) + par * 32, s, q);
            __syncwarp();
            if (w == 0) asm volatile("bar.arrive 6, 160;" ::: "memory");
            TS(1);
        }
#pragma unroll 1
        for (int it = 0; it < 4; it++) {
            const int cv = it >> 1, b = it & 1;
            uint4 A[4];
            mbar_wait(mb + 8 * (B_ROW + 4 * b + 3), cv);
            if (cv) {
#pragma unroll
                for (int u = 0; u < 4; u++) A[u] = ldg_nc((const char*)p.x + b * (1 << 20) + out_off + (u >> 1) * 65536 + (u & 1) * 64);
            } else {
                uint32_t e0, e1;
                int n = 0;
                do {
                    e0 = ldg_rlx32(p.box + BX_EMB + par * 1024 + b * 512 + och * 4);
                    e1 = ldg_rlx32(p.box + BX_EMB + par * 1024 + b * 512 + och * 4 + 32);
                } while (__any_sync(~0u, min(e0, e1) == 0u) && ++n < SPIN_LIMIT);
                e0 = pack_bf(__uint_as_float(e0), __uint_as_float(e0));
                e1 = pack_bf(__uint_as_float(e1), __uint_as_float(e1));
                A[0] = A[1] = make_uint4(e0, e0, e0, e0);
                A[2] = A[3] = make_uint4(e1, e1, e1, e1);
            }
            mbar_wait(mb + 8 * (B_P + it), 0);
#pragma unroll
            for (int u = 0; u < 4; u++) A[u] = add_unit(A[u], lds128(pa + b * 8192 + u * 2048));
            char* dst = (cv ? (char*)p.out : p.h + par * (2 << 20)) + b * (1 << 20) + out_off;
            mbar_wait(mb + 8 * (B_Q + it), 0);
            TS(4 + 4 * it);
#pragma unroll
            for (int u = 0; u < 4; u++) {
                A[u] = add_unit(A[u], lds128(pa + 16384 + b * 8192 + u * 2048));
                A[u].x = max(A[u].x, (uint32_t)(cv ^ 1));
                stg_rlx(dst + (u >> 1) * 65536 + (u & 1) * 64, A[u]);
            }
            TS2(5 + 4 * it);
            if (cv == 0) {
                float s[4] = {0.f, 0.f, 0.f, 0.f}, q[4] = {0.f, 0.f, 0.f, 0.f};
#pragma unroll
                for (int u = 0; u < 4; u++) {
                    const uint32_t r[4] = {A[u].x, A[u].y, A[u].z, A[u].w};
#pragma unroll
                    for (int i = 0; i < 4; i++) {
                        const float lo = bf_lo(r[i]), hi = bf_hi(r[i]);
                        s[i & 2] += lo; q[i & 2] = fmaf(lo, lo, q[i & 2]);
                        s[(i & 2) + 1] += hi; q[(i & 2) + 1] = fmaf(hi, hi, q[(i & 2) + 1]);
                    }
                }
                s[0] = (s[0] + s[1]) + (s[2] + s[3]); q[0] = (q[0] + q[1]) + (q[2] + q[3]);
                warp_sum2(s[0], q[0]);
                if (lane == 0) sts64f(sb + SM_RED + 2048 + b * 32 + w * 8, s[0], q[0]);
                bar_n(7, 128);
                if (w == 0) {
                    const uint4 v = lds128(sb + SM_RED + 2048 + b * 32 + (lane & 1) * 16);
                    if (lane < 2) red_stat(p.box + m * 512 + b * 256 + lane * 128 + par * 32 + 16, __uint_as_float(v.x) + __uint_as_float(v.z),
                                           __uint_as_float(v.y) + __uint_as_float(v.w));
                    __syncwarp();
                    asm volatile("{.reg .pred e; elect.sync _|e, 0xffffffff; @e mbarrier.arrive.shared::cta.b64 _, [%0];\n"
                                 "@e mbarrier.arrive.relaxed.cluster.shared::cluster.b64 _, [%1];}" ::"r"(mb + 8 * (B_FREE + b)), "r"(rbar + 8 * b) : "memory");
                }
                TS(6 + 4 * it);
            }
        }
    } else if (wid >= 12) {
        asm volatile("setmaxnreg.dec.sync.aligned.u32 48;");
        if (wid == 14) {
            TS(19);
            if (elect_one()) {
#pragma unroll
                for (int j = 0; j < 4; j++) mbar_init(mb + 8 * (B_W + j), 1);
#pragma unroll
                for (int j = 0; j < 4; j++) {
                    mbar_expect_tx(mb + 8 * (B_W + j), WPIECE);
                    tma3(sb + SM_WS + j * WPIECE, &tm.m[2], mb + 8 * (B_W + j), 64 * m + 16 * j, 9 * k);
                }
            }
            __syncwarp();
            TS2(20);
            asm volatile("bar.arrive 1, 160;" ::: "memory");
            asm volatile("barrier.cluster.arrive.relaxed.aligned;" ::: "memory");
            bar_n(5, 96);
#pragma unroll 1
            for (int j = 0; j < 8; j++) {
                constexpr uint64_t wa = (uint64_t)(B_W + XW0) | (uint64_t)(B_W + 3) << 8 | (uint64_t)B_STAT << 16 | (uint64_t)B_ROWA << 24 |
                                        (uint64_t)(B_ROWA + 7) << 32 | (uint64_t)(P1STAT ? B_STAT + 2 : B_X1) << 40 | (uint64_t)(B_WFREE + 1) << 48 |
                                        (uint64_t)(P1STAT ? B_STAT + 3 : B_X1) << 56;
                if (j >= 4) mbar_wait(mb + 8 * (B_FREE - 2 + (j >> 1)), 0);
                const uint32_t c0 = clock32();
                if (j >= XMODE) mbar_wait(mb + 8 * (uint32_t)((wa >> (8 * j)) & 63), 0);
                while (clock32() - c0 < (j < 4 ? 0 : ((j & 1) ? HDELAY2 : HDELAY))) { }
                const uint32_t dst = sb + (j < 4 ? SM_SA + j * 16384 : (j < 6 ? SM_SB : SM_WS) + (j & 1) * 16384);
                const int plane = (j & 2) * 64 + 64 * k + (j < 4 ? 0 : __float_as_uint(lds32f(sb + SM_PAR)) * 256);
                const uint32_t bar = mb + 8 * (B_S + j), rs = seq >> (4 * (j & 1));
                if (elect_one()) {
                    mbar_expect_tx(bar, 16384);
                    tma3(dst, &tm.m[j >> 2], bar, plane, img_row(t, rs));
                    tma3(dst + 8192, &tm.m[j >> 2], bar, plane, img_row(t, rs >> 2));
                }
                __syncwarp();
                TS2(j);
            }
            TS_DUMP();
            return;
        }
        if (wid == 12) {
            uint32_t tp = clock32() + PT0;
            const uint32_t oline = acc_off(idx >> 6, 0, (idx >> 5) & 1);
            const uint32_t c0 = ldg_rlx32(p.box + oline + 8), c1 = ldg_rlx32(p.box + oline + 40);
            uint32_t gb[4];
#pragma unroll
            for (int j = 0; j < 4; j++) asm volatile("ld.global.nc.u32 %0, [%1];" : "=r"(gb[j]) : "l"(p.gb[j] + 64 * k + 2 * lane));
            const int par = parity_of(c0, c1, 32.0f);
            asm volatile("st.shared.u32 [%0], %1;" ::"r"(sb + SM_PAR), "r"(par) : "memory");
            asm volatile("st.shared.v4.u32 [%0], {%1,%1,%1,%1};" ::"r"(sb + SM_COEF + 2048 + lane * 16), "r"(0) : "memory");
            asm volatile("barrier.cluster.arrive.relaxed.aligned;" ::: "memory");
            bar_n(3, 480);
            const uint32_t gl = (lane & 16) * 8 + par * 32;
#pragma unroll 1
            for (int gi = 0; gi < 4; gi++) {
                const int isH = gi >> 1;
                char* const bx = p.box + (gi & 1) * 256 + isH * 16;
                char* src = bx + k * 512 + gl;
                asm volatile("" : "+l"(src));
                if (isH) {
                    gb[0] = gb[2]; gb[1] = gb[3];
                    mbar_wait(mb + 8 * (B_FREE - 2 + gi), 0);
                    tp = clock32() + PDELAY;
                }
                TS(4 + gi * 2);
                const uint32_t want = isH ? 0x42800000u : 0x42000000u + gi * 0x40000u;
                uint4 v = make_uint4(0, 0, want, 0);
                while ((int)(clock32() - tp) < 0) { }
                int it = 0;
                do {
                    if ((lane & 15) == 0) v = ldg_rlx(src);
                } while (__any_sync(~0u, v.z != want) && ++it < SPIN_LIMIT);
                const float mean = __shfl_sync(~0u, __uint_as_float(v.x), lane & 16) * (1.0f / 131072.0f);
                const float msq = __shfl_sync(~0u, __uint_as_float(v.y), lane & 16) * (4.0f / 131072.0f);
                float rs;
                asm("rsqrt.approx.ftz.f32 %0, %1;" : "=f"(rs) : "f"(fmaxf(fmaf(-4.0f * mean, mean, msq), 0.f) + 4e-5f));
                const float a0 = rs * bf_lo(gb[0]), a1 = rs * bf_hi(gb[0]);
                const uint32_t ca0 = pack_bf(a0, a0), ca1 = pack_bf(a1, a1);
                const float b0 = fmaf(-mean, bf_hi(ca0), 0.5f * bf_lo(gb[1]));
                const float b1 = fmaf(-mean, bf_hi(ca1), 0.5f * bf_hi(gb[1]));
                asm volatile("st.shared.v4.u32 [%0], {%1,%2,%3,%4};" ::"r"(sb + SM_COEF + gi * 512 + lane * 16), "r"(ca0), "r"(pack_bf(b0, b0)),
                             "r"(ca1), "r"(pack_bf(b1, b1)) : "memory");
                __syncwarp();
                arrive_elect(mb + 8 * (B_STAT + gi));
                if ((idx | (lane & 15)) < 2 && (lane & 1) == 0) stg_rlx(bx + k * 512 + (gl ^ 32), make_uint4(0, 0, 0, 0));
                __syncwarp();
                TS(5 + gi * 2);
            }
        } else if (wid == 13) {
            if (elect_one()) {
                prefetch_tm(&tm.m[0]);
#pragma unroll
                for (int j = 0; j < B_W; j++) mbar_init(mb + 8 * j, j < B_Q ? 8 : (j < B_FREE ? 4 : 1));
#pragma unroll
                for (int j = 0; j < 4; j++) mbar_expect_tx(mb + 8 * (B_P + j), 8192);
                asm volatile("fence.mbarrier_init.release.cluster;" ::: "memory");
            }
            __syncwarp();
            TS2(20);
            asm volatile("bar.arrive 5, 96;" ::: "memory");
            asm volatile("bar.arrive 3, 480;" ::: "memory");
            asm volatile("barrier.cluster.arrive.relaxed.aligned;" ::: "memory");
            asm volatile("barrier.cluster.wait.aligned;" ::: "memory");
            uint32_t rbar;
            asm("mapa.shared::cluster.u32 %0, %1, %2;" : "=r"(rbar) : "r"(mb + 8 * B_PFREE), "r"(k ^ 1));
#pragma unroll 1
            for (int j = 0; j < 16; j++) {
                const int o = (j & 7) * 8;
                if ((j & 3) == 3) mbar_wait(mb + 8 * (B_PFREE + max((j >> 2) - 1, 0)), 0);
                mbar_wait(mb + 8 * B_ROWA + o, j >> 3);
                asm volatile(
                    "{\n"
                    ".reg .pred e, r;\n"
                    "fence.proxy.async.shared::cta;\n"
                    "elect.sync _|e, 0xffffffff;\n"
                    "@e mbarrier.arrive.shared::cta.b64 _, [%0];\n"
                    "setp.eq.and.u32 r, %2, 1, e;\n"
                    "@r mbarrier.arrive.relaxed.cluster.shared::cluster.b64 _, [%1];\n"
                    "}\n" ::"r"(mb + 8 * B_ROW + o), "r"(rbar), "r"(j) : "memory");
                TS2(j);
            }
        } else {
            asm volatile("barrier.cluster.arrive.relaxed.aligned;" ::: "memory");
            bar_n(5, 96);
            for (const uint32_t c0 = clock32(); clock32() - c0 < XD;) { }
            if (elect_one()) {
                mbar_expect_tx(mb + 8 * B_X1, 8192);
                asm volatile("cp.async.bulk.shared::cluster.global.mbarrier::complete_tx::bytes [%0], [%1], %2, [%3];"
                             ::"r"(sb + SM_SB + 24576), "l"((const char*)p.x + (128 + idx) * 8192), "r"(8192), "r"(mb + 8 * B_X1) : "memory");
                prefetch_tm(&tm.m[1]);
            }
            bar_n(3, 480);
            const int par = __float_as_uint(lds32f(sb + SM_PAR));
            mbar_wait(mb + 8 * B_WFREE, 0);
            mbar_wait(mb + 8 * (B_STAT + 1), 0);
            mbar_wait(mb + 8 * (B_ROW + 3), 0);
            if (elect_one()) {
#pragma unroll 1
                for (int j = 0; j < 4; j++) {
                    mbar_expect_tx(mb + 8 * (B_W + j), WPIECE);
                    tma3(sb + SM_WS + j * WPIECE, &tm.m[3], mb + 8 * (B_W + j), 64 * m + 16 * j, 9 * k);
                }
            }
            __syncwarp();
            mbar_wait(mb + 8 * (B_STAT + 3), 0);
            mbar_wait(mb + 8 * (B_ROW + 6), 1);
            uint4* oh = (uint4*)(p.h + (par ^ 1) * (2 << 20)) + idx * 1024 + lane;
#pragma unroll 1
            for (int u = 0; u < 32; u++) oh[u * 32] = make_uint4(0, 0, 0, 0);
        }
    } else if (wid >= 4) {
        const int ht = tid - 128, hw = wid - 4;
        asm volatile("barrier.cluster.arrive.relaxed.aligned;" ::: "memory");
        TS2(1);
        stat16(r0, r1, sb + SM_RED + (ht >> 1) * 8, lane);
        TS2(2);
        asm volatile("setmaxnreg.dec.sync.aligned.u32 64;");
        bar_n(3, 480);
        const int icl = (hw & 4) * 8 + (lane & 28) + (hw & 3);
        uint32_t st_lane = hw * CHUNK + (2 * (lane >> 3) + (lane & 1) + 1) * PLANE + ((lane >> 1) & 3) * 32;
        uint32_t dup_lane;
        {
            const int bd = ((lane >> 1) & 7) + ((lane & 1) ? 1 : -1);
            dup_lane = hw * CHUNK + ((lane & 1) ? 0 : 9 * PLANE) + (2 * (bd & 3) + ((bd >> 2) & 1)) * 16;
            if (bd < 0 || bd > 7) dup_lane = hw * CHUNK + PLANE + 16;
        }
        uint32_t ld0 = icl * 128 + (((lane & 3) ^ (icl & 7)) << 4), ld1 = ld0 ^ 64, cl = icl * 8;
        const int inv = t == 0 ? 3 - f : (t == 31 ? 1 + 2 * f : 4);
        asm volatile("" : "+r"(st_lane), "+r"(dup_lane), "+r"(ld0), "+r"(ld1), "+r"(cl));
        mbar_wait(mb + 8 * B_X1, 0);
        TS2(3);
        stat16(lds128(sb + SM_SB + 24576 + ht * 16), lds128(sb + SM_SB + 28672 + ht * 16), sb + SM_RED + 1024 + (ht >> 1) * 8, lane);
        asm volatile("bar.arrive 4, 288;" ::: "memory");
        TS2(20);
        uint4 X[4];
        float2 C[2];
        uint32_t stage = sb + SM_SA, coefA = sb + SM_COEF, coefB = sb + SM_COEF + (inv == 1 ? 2048 : 0);
        uint32_t cbar = mb + 8 * B_STAT;
        bool have = false, havec = false;
#pragma unroll 1
        for (int gp = 0; gp < 8; gp++) {
            const uint32_t rs = seq >> (4 * (gp & 1));
            if (!havec) {
              if (!have) {
                mbar_wait(mb + 8 * (B_S + gp), 0);
                TS2(21 + gp);
                X[0] = lds128(stage + ld0); X[1] = lds128(stage + ld1);
                X[2] = lds128(stage + 8192 + ld0); X[3] = lds128(stage + 8192 + ld1);
#pragma unroll 1
                for (int it = 0; gp >= 4 && __any_sync(~0u, min(min(X[0].x, X[1].x), min(X[2].x, X[3].x)) == 0u) && it < SPIN_LIMIT; it++) {
                    const char* src = p.h + (__float_as_uint(lds32f(sb + SM_PAR)) * 2 + ((gp >> 1) & 1)) * (1 << 20) + (64 * k + icl) * 8192 + (lane & 3) * 16;
                    const char* sa = src + img_row(t, rs) * 128;
                    const char* sc = src + img_row(t, rs >> 2) * 128;
                    X[0] = ldg_rlx(sa); X[1] = ldg_rlx(sa + 64);
                    X[2] = ldg_rlx(sc); X[3] = ldg_rlx(sc + 64);
                }
              }
                mbar_wait(cbar, 0);
                C[0] = lds64f(coefA + cl);
                C[1] = lds64f(coefB + cl);
            }
            const uint32_t opb = sb + SM_OP0 - (gp & 2) * (OPSZ / 2), abar = mb + 8 * B_ROWA + (gp & 3) * 16;
            uint32_t h[16];
#pragma unroll
            for (int u = 0; u < 4; u++) {
                const uint32_t ca = __float_as_uint(C[u >> 1].x), cb = __float_as_uint(C[u >> 1].y);
                h[4 * u] = fmabf2(X[u].x, ca, cb); h[4 * u + 1] = fmabf2(X[u].y, ca, cb);
                h[4 * u + 2] = fmabf2(X[u].z, ca, cb); h[4 * u + 3] = fmabf2(X[u].w, ca, cb);
            }
#pragma unroll
            for (int r = 0; r < 2; r++) {
                const uint32_t u0 = opb + ((rs >> (2 * r)) & 3) * 128;
                uint32_t* g = h + 8 * r;
#pragma unroll
                for (int i = 0; i < 8; i++) {
                    uint32_t th;
                    asm volatile("tanh.approx.bf16x2 %0, %1;" : "=r"(th) : "r"(g[i]));
                    g[i] = fmabf2(g[i], th, g[i]);
                }
                stsm4t(u0 + st_lane, g[0], g[1], g[2], g[3]);
                asm volatile("stmatrix.sync.aligned.m8n8.x2.trans.shared.b16 [%0], {%1,%2};"
                             ::"r"(u0 + dup_lane), "r"(__byte_perm(g[0], g[3], 0x7610)), "r"(__byte_perm(g[4], g[7], 0x7610)) : "memory");
                stsm4t(u0 + st_lane + 16, g[4], g[5], g[6], g[7]);
                arrive_elect(abar + 8 * r);
                TS(4 + 2 * gp + r);
                if (r == 0) {
                    stage += gp == 3 ? -16384 : (gp == 5 ? SM_WS - SM_SB - 16384 : 16384);
                    const uint32_t ct = sb + SM_COEF + ((gp + 1) >> 1) * 512, i0 = 2 * ((gp + 1) & 1);
                    coefA = i0 == inv ? sb + SM_COEF + 2048 : ct;
                    coefB = i0 + 1 == inv ? sb + SM_COEF + 2048 : ct;
                    cbar = mb + 8 * (HOLD && gp == 4 ? B_WFREE + 1 : B_STAT + ((gp + 1) >> 1));
                    const bool nx = mbar_test(mb + 8 * (B_S + gp + 1), 0), ns = mbar_test(cbar, 0);
                    X[0].x = 0;
                    asm volatile(
                        "{\n"
                        ".reg .pred p, c;\n"
                        "setp.ne.u32 p, %24, 0;\n"
                        "setp.ne.u32 c, %25, 0;\n"
                        "@p ld.shared.v4.u32 {%0,%1,%2,%3}, [%20];\n"
                        "@p ld.shared.v4.u32 {%4,%5,%6,%7}, [%21];\n"
                        "@p ld.shared.v4.u32 {%8,%9,%10,%11}, [%20+8192];\n"
                        "@p ld.shared.v4.u32 {%12,%13,%14,%15}, [%21+8192];\n"
                        "@c ld.shared.v2.f32 {%16,%17}, [%22];\n"
                        "@c ld.shared.v2.f32 {%18,%19}, [%23];\n"
                        "}\n"
                        : "+r"(X[0].x), "=r"(X[0].y), "=r"(X[0].z), "=r"(X[0].w), "=r"(X[1].x), "=r"(X[1].y), "=r"(X[1].z), "=r"(X[1].w),
                          "=r"(X[2].x), "=r"(X[2].y), "=r"(X[2].z), "=r"(X[2].w), "=r"(X[3].x), "=r"(X[3].y), "=r"(X[3].z), "=r"(X[3].w),
                          "=f"(C[0].x), "=f"(C[0].y), "=f"(C[1].x), "=f"(C[1].y)
                        : "r"(stage + ld0), "r"(stage + ld1), "r"(coefA + cl), "r"(coefB + cl), "r"((uint32_t)nx), "r"((uint32_t)ns) : "memory");
                    havec = ns;
                }
            }
            have = __all_sync(~0u, min(min(X[0].x, X[1].x), min(X[2].x, X[3].x)) != 0u);
            havec = __all_sync(~0u, havec) && have;
        }
    } else {
        const uint32_t t16 = tid * 16;
        {
            const uint32_t a = sb + SM_OP1 + (tid >> 3) * CHUNK + ((tid >> 1) & 3) * 128 + ((tid & 1) ? 9 * PLANE + 7 * 16 : 0);
            asm volatile("st.shared.v4.u32 [%0], {%1,%1,%1,%1};" ::"r"(a), "r"(0) : "memory");
            asm volatile("fence.proxy.async.shared::cta;" ::: "memory");
            asm volatile("barrier.cluster.arrive.relaxed.aligned;" ::: "memory");
        }
        bar_n(1, 160);
        bar_n(6, 160);
        asm volatile("setmaxnreg.inc.sync.aligned.u32 240;");
        uint32_t W[144];
        float accS[32], accF[32];
        uint32_t rsb;
        asm("mapa.shared::cluster.u32 %0, %1, %2;" : "=r"(rsb) : "r"(sb), "r"(k ^ 1));
        const uint64_t dconst = ((uint64_t)(CHUNK / 16) << 16) | ((uint64_t)(PLANE / 16) << 32);
        const uint32_t d0 = (((sb + SM_OP0) & 0x3ffff) >> 4) + cen * 8;
#define HANDOVER(slot, bar, on) do { _Pragma("unroll") for (int u = 0; u < 4; u++) { const uint4 o = pack_unit(accF, u); \
        asm volatile("{.reg .pred p; setp.ne.u32 p, %5, 0; @p st.shared.v4.u32 [%0], {%1,%2,%3,%4};}" \
        ::"r"(sb + SM_SA + 16384 + (slot) * 8192 + u * 2048 + t16), "r"(o.x), "r"(o.y), "r"(o.z), "r"(o.w), "r"((uint32_t)(on)) : "memory"); } \
        asm volatile("{.reg .pred e; elect.sync _|e, 0xffffffff; setp.ne.and.u32 e, %1, 0, e; @e mbarrier.arrive.shared::cta.b64 _, [%0];}" \
        ::"r"(bar), "r"((uint32_t)(on)) : "memory"); } while (0)
#pragma unroll 1
        for (int cv = 0; cv < 2; cv++) {
            {
                uint32_t lo = (lane & 3) * 2048 + ((lane >> 3) + (lane & 4)) * 128;
                asm volatile("" : "+r"(lo));
                mbar_wait_t(false, mb + 8 * (B_W + wid), cv);
                TS2(3);
                uint32_t seg[72];
                load_raw<0>(seg, sb + SM_WS + wid * WPIECE, lo);
                permute_raw(seg, W);
                load_raw<1>(seg, sb + SM_WS + wid * WPIECE, lo);
                permute_raw(seg, W + 72);
                arrive_elect(mb + 8 * (B_WFREE + cv));
                TS2(4);
            }
#pragma unroll
            for (int i = 0; i < 32; i++) accF[i] = 0.f;
#pragma unroll 1
            for (int b = 0; b < 2; b++) {
                const int it = 2 * cv + b;
                const uint32_t rb = mb + 8 * B_ROW + b * 32;
                const uint64_t dS = dconst | (uint64_t)(d0 - b * (OPSZ / 16));
                const uint64_t dF = dS + (uint64_t)(int64_t)(16 * f - 8);
                asm volatile(
                    "{\n"
                    ".reg .pred p;\n"
                    ".reg .u32 n;\n"
                    "mbarrier.test_wait.parity.shared::cta.b64 p, [%0], %2;\n"
                    "@p bra.uni ROW_DONE;\n"
                    "mov.u32 n, 0;\n"
                    "ROW_LOOP:\n"
                    "mbarrier.try_wait.parity.shared::cta.b64 p, [%1], %2;\n"
                    "@p bra.uni ROW_FENCE;\n"
                    "add.u32 n, n, 1;\n"
                    "setp.lt.u32 p, n, 100000;\n"
                    "@p bra.uni ROW_LOOP;\n"
                    "trap;\n"
                    "ROW_FENCE:\n"
                    "fence.proxy.async.shared::cta;\n"
                    "ROW_DONE:\n"
                    "}\n" ::"r"(rb), "r"(rb - 8 * (B_ROW - B_ROWA)), "r"(cv) : "memory");
                TS(8 + 4 * it);
                wg_fence();
                mma_sub<0>(accS, W, dS);
                mma_sub<1>(accS, W, dS);
                mma_sub<2>(accS, W, dS);
                wg_commit();
                wg_wait<1>();
                acc_fence(accF);
                HANDOVER(0, mb + 8 * (B_Q + 2 * cv), b);
                bool ok = mbar_test(rb + 8, cv);
                mma_sub<3>(accS, W, dS);
                mbar_wait_t(ok, rb + 8, cv);
                TS3(1);
                wg_fence();
                mma_sub<4>(accS, W, dS);
                mma_sub<5>(accS, W, dS);
                mma_sub<6>(accS, W, dS);
                ok = mbar_test(rb + 16, cv);
                mma_sub<7>(accS, W, dS);
                mbar_wait_t(ok, rb + 16, cv);
                TS3(7);
                wg_fence();
                mma_sub<8>(accS, W, dS);
                mma_sub<9>(accS, W, dS);
                mma_sub<10>(accS, W, dS);
                mma_sub<11>(accS, W, dS);
                wg_commit();
                TS2(10 + 4 * it);
                wg_fence();
                mma_sub<0>(accF, W, dF);
                mma_sub<1>(accF, W, dF);
                ok = mbar_test(rb + 24, cv);
                mma_sub<2>(accF, W, dF);
                wg_commit();
                mbar_wait_t(ok, rb + 24, cv);
                wg_wait<1>();
                acc_fence(accS);
                TS3(25);
#pragma unroll
                for (int u = 0; u < 4; u++) {
                    const uint4 o = pack_unit(accS, u);
                    send16(rsb + SM_SA + b * 8192 + u * 2048 + t16, rsb + SM_MISC + 8 * (B_P + it), o.x, o.y, o.z, o.w);
                }
                TS3(26);
                wg_fence();
                mma_sub<3>(accF, W, dF);
                mma_sub<4>(accF, W, dF);
                mma_sub<5>(accF, W, dF);
                mma_sub<6>(accF, W, dF);
                mma_sub<7>(accF, W, dF);
                mma_sub<8>(accF, W, dF);
                mma_sub<9>(accF, W, dF);
                mma_sub<10>(accF, W, dF);
                mma_sub<11>(accF, W, dF);
                wg_commit();
                TS2(11 + 4 * it);
            }
            wg_wait<0>();
            acc_fence(accF);
            HANDOVER(1, mb + 8 * (B_Q + 2 * cv + 1), 1);
        }
    }
    TS(0);
    TS_DUMP();
}

typedef CUresult (*EncodeFn)(CUtensorMap*, CUtensorMapDataType, cuuint32_t, void*, const cuuint64_t*, const cuuint64_t*,
                             const cuuint32_t*, const cuuint32_t*, CUtensorMapInterleave, CUtensorMapSwizzle,
                             CUtensorMapL2promotion, CUtensorMapFloatOOBfill);

void make_wmap(EncodeFn enc, CUtensorMap* tm, void* w) {
    cuuint64_t gd[3] = {64, 128, 18};
    cuuint64_t gs[2] = {2304, 128};
    cuuint32_t bd[3] = {64, 16, 9};
    cuuint32_t es[3] = {1, 1, 1};
    enc(tm, CU_TENSOR_MAP_DATA_TYPE_BFLOAT16, 3, w, gd, gs, bd, es, CU_TENSOR_MAP_INTERLEAVE_NONE,
        CU_TENSOR_MAP_SWIZZLE_128B, CU_TENSOR_MAP_L2_PROMOTION_L2_128B, CU_TENSOR_MAP_FLOAT_OOB_FILL_NONE);
}

void make_amap(EncodeFn enc, CUtensorMap* tm, void* a, int planes, int rows) {
    cuuint64_t gd[3] = {64, (cuuint64_t)planes, 64};
    cuuint64_t gs[2] = {8192, 128};
    cuuint32_t bd[3] = {64, 64, (cuuint32_t)rows};
    cuuint32_t es[3] = {1, 1, 1};
    enc(tm, CU_TENSOR_MAP_DATA_TYPE_BFLOAT16, 3, a, gd, gs, bd, es, CU_TENSOR_MAP_INTERLEAVE_NONE,
        CU_TENSOR_MAP_SWIZZLE_128B, CU_TENSOR_MAP_L2_PROMOTION_L2_128B, CU_TENSOR_MAP_FLOAT_OOB_FILL_NONE);
}

}

extern "C" void kernel_launch(void* const* d_in, const int* in_sizes, int n_in, void* d_out, int out_size) {
    static EncodeFn enc = nullptr;
    static void *ph, *pbox;
    if (!enc) {
        cudaGetSymbolAddress(&ph, g_h);
        cudaGetSymbolAddress(&pbox, g_box);
        void* fn = nullptr;
        cudaDriverEntryPointQueryResult qr;
        cudaGetDriverEntryPoint("cuTensorMapEncodeTiled", &fn, cudaEnableDefault, &qr);
        enc = (EncodeFn)fn;
        cudaFuncSetAttribute(resblock_kernel, cudaFuncAttributeMaxDynamicSharedMemorySize, SMEM_BYTES);
    }
    Params p;
    p.x = (const __nv_bfloat16*)d_in[0];
    p.t_emb = (const __nv_bfloat16*)d_in[1];
    p.gb[0] = (const __nv_bfloat16*)d_in[2];
    p.gb[1] = (const __nv_bfloat16*)d_in[3];
    p.gb[2] = (const __nv_bfloat16*)d_in[6];
    p.gb[3] = (const __nv_bfloat16*)d_in[7];
    p.out = (__nv_bfloat16*)d_out;
    p.h = (char*)ph;
    p.box = (char*)pbox;
    Maps tm;
    {
        cuuint64_t gd[2] = {128, 768};
        cuuint64_t gs[1] = {256};
        cuuint32_t bd[2] = {32, 256};
        cuuint32_t es[2] = {1, 1};
        enc(&tm.m[4], CU_TENSOR_MAP_DATA_TYPE_BFLOAT16, 2, d_in[5], gd, gs, bd, es, CU_TENSOR_MAP_INTERLEAVE_NONE,
            CU_TENSOR_MAP_SWIZZLE_NONE, CU_TENSOR_MAP_L2_PROMOTION_NONE, CU_TENSOR_MAP_FLOAT_OOB_FILL_NONE);
    }
    make_amap(enc, &tm.m[0], d_in[0], 256, 1);
    make_amap(enc, &tm.m[1], ph, 512, 1);
    make_wmap(enc, &tm.m[2], d_in[4]);
    make_wmap(enc, &tm.m[3], d_in[8]);
    resblock_kernel<<<132, 640, SMEM_BYTES>>>(p, tm);
}
```
